```python
import torch

def _softmax(x, axis=-1):
    return torch.softmax(x, dim=axis)
def _gelu(x):
    return torch.nn.functional.gelu(x, approximate="tanh")
def _silu(x):
    return torch.nn.functional.silu(x)
def _sigmoid(x):
    return torch.sigmoid(x)
def _layernorm(x, axis=-1, eps=1e-5):
    m = x.mean(dim=axis, keepdim=True)
    v = x.var(dim=axis, keepdim=True, unbiased=False)
    return (x - m) / torch.sqrt(v + eps)
def _scatter_add(tgt, idx, src, axis=0):
    return tgt.clone().index_add_(axis, idx, src)
def _segment_sum(src, seg, n):
    out = torch.zeros((n,) + src.shape[1:], dtype=src.dtype)
    return out.index_add_(0, seg, src)
def _pad(x, pw):
    flat = tuple(v for pair in reversed(pw) for v in pair)
    return torch.nn.functional.pad(x, flat)

kernel_name = 'recurrent_scan__spectral_gfnet__mixer_token_mlp__prompt'

def setup_inputs():

    _w = (lambda a: (lambda t: t.to(torch.bfloat16) if t.is_floating_point() else t)(torch.as_tensor(a)))
    def _A_setup():
        B, S, D = 1, 2048, 512
        Df = D // 2 + 1
        return {
            "x": _w((lambda *s: torch.randn(*s, dtype=torch.bfloat16) * 0.05)(B, S, D)),
            "w_r": _w((lambda *s: torch.randn(*s, dtype=torch.bfloat16) * 0.8)(S, Df) * 0.02),
            "w_i": _w((lambda *s: torch.randn(*s, dtype=torch.bfloat16) * 0.8)(S, Df) * 0.02),
        }
    _A_in = _A_setup()

    def _B_setup():
        B, S, D, F = 1, 2048, 512, 1792
        return {
            "x": _w((lambda *s: torch.randn(*s, dtype=torch.bfloat16) * 0.05)(B, S, D)),
            "w1": _w((lambda *s: torch.randn(*s, dtype=torch.bfloat16) * 1.6)(S, F) * (S ** -0.5)),
            "b1": _w((lambda *s: torch.randn(*s, dtype=torch.bfloat16) * 12.8)(F) * 0.02),
            "w2": _w((lambda *s: torch.randn(*s, dtype=torch.bfloat16) * 0.4)(F, S) * (F ** -0.5)),
            "b2": _w((lambda *s: torch.randn(*s, dtype=torch.bfloat16) * 6.4)(S) * 0.02),
        }
    _B_in = _B_setup()

    return {
        "A_x": _A_in["x"],
        "A_w_r": _A_in["w_r"],
        "A_w_i": _A_in["w_i"],
        "B_x": _B_in["x"],
        "B_w1": _B_in["w1"],
        "B_b1": _B_in["b1"],
        "B_w2": _B_in["w2"],
        "B_b2": _B_in["b2"],
    }

def reference(A_x, A_w_r, A_w_i, B_x, B_w1, B_b1, B_w2, B_b2):
    def _A_ref(x, w_r, w_i):
        B, S, D = x.shape
        X = (lambda x, axes=(-2,-1): torch.fft.rfft2(x.float(), dim=axes))(x, axes=(-2, -1))
        W = w_r + 1j * w_i
        X = X * W
        y = (lambda x, s, axes=(-2,-1): torch.fft.irfft2(x, s=s, dim=axes).to(torch.bfloat16))(X, (S, D), axes=(-2, -1))
        return y

    def _B_ref(x, w1, b1, w2, b2):
        B, S, D = x.shape
        h = _layernorm(x, axis=-1)
        u = torch.einsum("bsd,sf->bdf", h, w1) + b1
        u = _gelu(u)
        y = torch.einsum("bdf,fs->bds", u, w2) + b2
        return (lambda x, *d: x.permute(*d))(y, 0, 2, 1)

    x = A_x
    xn = _layernorm(x, axis=-1)
    s = _A_ref(xn, A_w_r, A_w_i)
    g = _silu(_B_ref(xn, B_w1, B_b1, B_w2, B_b2))
    return x + s * g
```

```cpp
#include <cuda_runtime.h>
#include <cuda_bf16.h>
#include <cuda.h>
#include <stdint.h>

#define PF_T0 0
#define X1_DT 500
#define TM 4
#define ZK 8
#define SIG_MODE 0
#define H_LATE 2
#define CST 2
#define CST0 0
#define CONST_POS 2
#define G_POS 0
#define ZST 2
#define SM_MAP 1

namespace {

constexpr int SEQ = 2048, DM = 512, FF = 1792, DF = 257;
constexpr int NCTA = 132;
constexpr int NTHR = 512;
constexpr int SLOT = 16384;
constexpr int NS = 5, STAGE = 2 * SLOT;
constexpr int S0 = 10 * SLOT, S1 = 11 * SLOT, S2 = 12 * SLOT, S3 = 13 * SLOT;
constexpr int WCH = 16512;
constexpr int XTRA = 14 * SLOT;
constexpr int MISC = 14 * SLOT + 128;
constexpr int BIAS = 14 * SLOT + 512;
constexpr int EPSV = 14 * SLOT + 1008;
constexpr int RMAT = 14 * SLOT + 1024;
constexpr int SMEM_BYTES = RMAT + 2048;

constexpr int B_FULL = 0, B_EMPTY = NS, B_NONE = 2 * NS, B_WCH = 11, B_WDONE = 19, B_STG = 20, B_S4 = 21, B_G = 22, B_B1 = 23,
              B_WQ = 24, B_XFREE1 = 25, B_XFREE2 = 26, B_XFULL1 = 27, B_XFULL2 = 28, B_Z = 29, B_FIN = 30, B_S1 = 31,
              B_BIAS = 32, B_COUNT = 33;
constexpr int NB_H = 1, NB_U = 2, NB_Z = 3, NB_C = 4, NB_HLP = 5, NB_R = 6, NB_S = 7;

constexpr int G_H = 0;
constexpr int G_U = G_H + 128 * SLOT;
constexpr int G_Z = G_U + 112 * SLOT;
constexpr int G_S = G_Z + 128 * SLOT;
constexpr int G_X1 = G_S + 128 * SLOT;
constexpr int G_WT = G_X1 + 129 * SLOT;
constexpr int G_CNT = G_WT + DF * SEQ * 4;
constexpr int C_H = 0, C_X = 2, C_W = 3, C_Z = 4, C_EPOCH = 5, C_U = 6, C_S = 14, C_COUNT = 30;
constexpr int G_PROF = G_CNT + C_COUNT * 128;
__device__ __align__(1024) unsigned char g_scr[G_PROF + NCTA * 192 * 8];

#define STAMP(id) do {} while (0)
#define GSTAMP(id) do {} while (0)

__device__ __forceinline__ void mbar_init(uint32_t b, int c) {
  asm volatile("mbarrier.init.shared::cta.b64 [%0], %1;" ::"r"(b), "r"(c) : "memory");
}
__device__ __forceinline__ void mbar_expect(uint32_t b, int bytes) {
  asm volatile("mbarrier.arrive.expect_tx.shared::cta.b64 _, [%0], %1;" ::"r"(b), "r"(bytes) : "memory");
}
__device__ __forceinline__ void mbar_arrive(uint32_t b) {
  asm volatile("mbarrier.arrive.shared::cta.b64 _, [%0];" ::"r"(b) : "memory");
}
__device__ __forceinline__ void mbar_arrive_cluster(uint32_t remote) {
  asm volatile("mbarrier.arrive.shared::cluster.b64 _, [%0];" ::"r"(remote) : "memory");
}
#define STR2(x) #x
#define STR(x) STR2(x)
#define PSLEEP ""
#define HINT ""
__device__ __forceinline__ void mbar_wait(uint32_t b, int ph = 0) {
  asm volatile("{\n.reg .pred p;\n.reg .u32 n;\n"
               "mbarrier.try_wait.parity.shared::cta.b64 p, [%0], %1;\n@p bra WD;\n"
               "mov.u32 n, 0;\nWL:\n"
               "mbarrier.try_wait.parity.shared::cta.b64 p, [%0], %1" HINT ";\n@p bra WD;\n"
               "add.u32 n, n, 1;\nsetp.lt.u32 p, n, 0x100000;\n@p bra WL;\ntrap;\nWD:\n}" ::"r"(b), "r"(ph) : "memory");
}
__device__ __forceinline__ bool elect_one() {
  uint32_t p;
  asm volatile("{\n.reg .pred e;\nelect.sync _|e, 0xffffffff;\nselp.u32 %0, 1, 0, e;\n}" : "=r"(p));
  return p;
}
__device__ __forceinline__ uint32_t mapa(uint32_t a, uint32_t cta) {
  uint32_t r;
  asm("mapa.shared::cluster.u32 %0, %1, %2;" : "=r"(r) : "r"(a), "r"(cta));
  return r;
}
__device__ __forceinline__ void tma2d(uint32_t dst, const CUtensorMap* m, int c0, int c1, uint32_t bar) {
  asm volatile("cp.async.bulk.tensor.2d.shared::cluster.global.mbarrier::complete_tx::bytes [%0], [%1, {%3, %4}], [%2];"
               ::"r"(dst), "l"(m), "r"(bar), "r"(c0), "r"(c1) : "memory");
}
__device__ __forceinline__ void tma2d_store(const CUtensorMap* m, int c0, int c1, uint32_t src) {
  asm volatile("cp.async.bulk.tensor.2d.global.shared::cta.bulk_group [%0, {%2, %3}], [%1];"
               ::"l"(m), "r"(src), "r"(c0), "r"(c1) : "memory");
}
__device__ __forceinline__ void bulk_load(uint32_t dst, const void* src, int bytes, uint32_t bar) {
  asm volatile("cp.async.bulk.shared::cluster.global.mbarrier::complete_tx::bytes [%0], [%1], %2, [%3];"
               ::"r"(dst), "l"(src), "r"(bytes), "r"(bar) : "memory");
}
__device__ __forceinline__ void bulk_store(void* dst, uint32_t src, int bytes) {
  asm volatile("cp.async.bulk.global.shared::cta.bulk_group [%0], [%1], %2;" ::"l"(dst), "r"(src), "r"(bytes) : "memory");
}
__device__ __forceinline__ void bulk_commit() { asm volatile("cp.async.bulk.commit_group;" ::: "memory"); }
__device__ __forceinline__ void bulk_wait_read() { asm volatile("cp.async.bulk.wait_group.read 0;" ::: "memory"); }
__device__ __forceinline__ void bulk_wait_all() { asm volatile("cp.async.bulk.wait_group 0;" ::: "memory"); }
__device__ __forceinline__ void fence_async_smem() { asm volatile("fence.proxy.async.shared::cta;" ::: "memory"); }
__device__ __forceinline__ void prefetch_map(const CUtensorMap* m) {
  asm volatile("prefetch.tensormap [%0];" ::"l"(m) : "memory");
}
__device__ __forceinline__ void nb_sync(int id, int n) { asm volatile("bar.sync %0, %1;" ::"r"(id), "r"(n) : "memory"); }
__device__ __forceinline__ void nb_arrive(int id, int n) { asm volatile("bar.arrive %0, %1;" ::"r"(id), "r"(n) : "memory"); }
__device__ __forceinline__ void signal(const void* cnt, unsigned inc) {
  asm volatile("fence.proxy.async;\nred.relaxed.gpu.global.add.u32 [%0], %1;" ::"l"(cnt), "r"(inc) : "memory");
}
__device__ __forceinline__ unsigned ld_relaxed(const void* p) {
  unsigned v;
  asm volatile("ld.relaxed.gpu.global.u32 %0, [%1];" : "=r"(v) : "l"(p) : "memory");
  return v;
}
__device__ __forceinline__ void poll(const void* cnt, unsigned base, unsigned mask, unsigned& seen) {
  asm volatile("{\n.reg .pred p;\n.reg .u32 n, v;\nand.b32 v, %0, %3;\nsetp.ne.u32 p, v, 0;\n@p bra PD;\nmov.u32 n, 0;\nPL:\n"
               "ld.relaxed.gpu.global.u32 v, [%1];\nsub.u32 %0, v, %2;\nand.b32 v, %0, %3;\nsetp.ne.u32 p, v, 0;\n@p bra PD;\n"
               PSLEEP "add.u32 n, n, 1;\nsetp.lt.u32 p, n, 0x200000;\n@p bra PL;\ntrap;\nPD:\n}"
               : "+r"(seen) : "l"(cnt), "r"(base), "r"(mask) : "memory");
}
__device__ __forceinline__ void poll(const void* cnt, unsigned base, unsigned mask) {
  unsigned seen = 0;
  poll(cnt, base, mask, seen);
}
__device__ __forceinline__ void stg32(void* p, uint32_t a) { asm volatile("st.global.u32 [%0], %1;" ::"l"(p), "r"(a) : "memory"); }
__device__ __forceinline__ void stg64(void* p, uint32_t a, uint32_t b) {
  asm volatile("st.global.v2.u32 [%0], {%1,%2};" ::"l"(p), "r"(a), "r"(b) : "memory");
}
__device__ __forceinline__ uint32_t pack(float lo, float hi) {
  uint32_t r;
  asm("cvt.rn.bf16x2.f32 %0, %1, %2;" : "=r"(r) : "f"(hi), "f"(lo));
  return r;
}
__device__ __forceinline__ float blo(uint32_t v) { return __uint_as_float(v << 16); }
__device__ __forceinline__ float bhi(uint32_t v) { return __uint_as_float(v & 0xffff0000u); }
__device__ __forceinline__ float rsqrt_fast(float x) {
  float r;
  asm("rsqrt.approx.f32 %0, %1;" : "=f"(r) : "f"(x));
  return r;
}
__device__ __forceinline__ float tanh_fast(float x) {
  float r;
  asm("tanh.approx.f32 %0, %1;" : "=f"(r) : "f"(x));
  return r;
}
__device__ __forceinline__ uint32_t movm(uint32_t a) {
  uint32_t d;
  asm("movmatrix.sync.aligned.m8n8.trans.b16 %0, %1;" : "=r"(d) : "r"(a));
  return d;
}
__device__ __forceinline__ void stsm4(uint32_t a, uint32_t r0, uint32_t r1, uint32_t r2, uint32_t r3) {
  asm volatile("stmatrix.sync.aligned.m8n8.x4.shared.b16 [%0], {%1,%2,%3,%4};" ::"r"(a), "r"(r0), "r"(r1), "r"(r2), "r"(r3) : "memory");
}
__device__ __forceinline__ void ldsm4(uint32_t a, uint32_t* r) {
  asm volatile("ldmatrix.sync.aligned.m8n8.x4.shared.b16 {%0,%1,%2,%3}, [%4];"
               : "=r"(r[0]), "=r"(r[1]), "=r"(r[2]), "=r"(r[3]) : "r"(a) : "memory");
}
__device__ __forceinline__ void st_async4(uint32_t a, uint32_t r0, uint32_t r1, uint32_t r2, uint32_t r3, uint32_t bar) {
  asm volatile("st.async.weak.shared::cluster.mbarrier::complete_tx::bytes.v4.b32 [%0], {%1,%2,%3,%4}, [%5];"
               ::"r"(a), "r"(r0), "r"(r1), "r"(r2), "r"(r3), "r"(bar) : "memory");
}
__device__ __forceinline__ uint4 lds128(uint32_t a) {
  uint4 v;
  asm volatile("ld.shared.v4.u32 {%0,%1,%2,%3}, [%4];" : "=r"(v.x), "=r"(v.y), "=r"(v.z), "=r"(v.w) : "r"(a) : "memory");
  return v;
}
__device__ __forceinline__ uint32_t lds32(uint32_t a) {
  uint32_t v;
  asm volatile("ld.shared.u32 %0, [%1];" : "=r"(v) : "r"(a) : "memory");
  return v;
}
__device__ __forceinline__ uint32_t clk() {
  uint32_t c;
  asm volatile("mov.u32 %0, %%clock;" : "=r"(c));
  return c;
}
__device__ __forceinline__ void wait_until(uint32_t t0, int dt) {
  while ((int)(clk() - t0) < dt) {
  }
}
__device__ __forceinline__ uint32_t dlo(uint32_t addr, uint32_t lbo) { return ((addr & 0x3FFFF) >> 4) | ((lbo >> 4) << 16); }
__host__ __device__ constexpr uint32_t dhi(uint32_t sbo, uint32_t sw) { return (sbo >> 4) | (sw << 30); }
__device__ __forceinline__ void wg_fence() { asm volatile("wgmma.fence.sync.aligned;" ::: "memory"); }
__device__ __forceinline__ void wg_commit() { asm volatile("wgmma.commit_group.sync.aligned;" ::: "memory"); }
template <int N> __device__ __forceinline__ void wg_wait() { asm volatile("wgmma.wait_group.sync.aligned %0;" ::"n"(N) : "memory"); }
template <int N> __device__ __forceinline__ void keep(float* d) {
#pragma unroll
  for (int i = 0; i < N; i++) asm volatile("" : "+f"(d[i])::"memory");
}
template <int N> __device__ __forceinline__ void renew(float* d) {
#pragma unroll
  for (int i = 0; i < N; i++) asm volatile("mov.b32 %0, %1;" : "=f"(d[i]) : "f"(d[i]) : "memory");
}
template <int N> __device__ __forceinline__ void pin(const void* v, uint32_t zero) {
  const uint32_t* d = (const uint32_t*)v;
#pragma unroll
  for (int i = 0; i < N; i += 4)
    asm volatile("{\n.reg .pred p;\nsetp.ne.u32 p, %4, 0;\n@p st.shared.v4.b32 [%4], {%0,%1,%2,%3};\n}"
                 ::"r"(d[i]), "r"(d[i + 1]), "r"(d[i + 2]), "r"(d[i + 3]), "r"(zero) : "memory");
}
template <int N> __device__ __forceinline__ void keepu(uint32_t* d) {
#pragma unroll
  for (int i = 0; i < N; i++) asm volatile("" : "+r"(d[i])::"memory");
}
#define R8(c, o) c(d[o]), c(d[o + 1]), c(d[o + 2]), c(d[o + 3]), c(d[o + 4]), c(d[o + 5]), c(d[o + 6]), c(d[o + 7])
#define D32 "%0,%1,%2,%3,%4,%5,%6,%7,%8,%9,%10,%11,%12,%13,%14,%15,%16,%17,%18,%19,%20,%21,%22,%23,%24,%25,%26,%27,%28,%29,%30,%31"
template <int TB> __device__ __forceinline__ void wgmma64(float* d, uint32_t a, uint32_t b) {
  asm volatile("{\n.reg .b64 da, db;\nmov.b64 da, {%32, %35};\nmov.b64 db, {%33, %36};\n"
               "wgmma.mma_async.sync.aligned.m64n64k16.f32.bf16.bf16 {" D32 "}, da, db, 1, 1, 1, 1, %34;\n}"
               : R8("+f", 0), R8("+f", 8), R8("+f", 16), R8("+f", 24)
               : "r"(a), "r"(b), "n"(TB), "n"(dhi(1024, 1)), "n"(dhi(1024, TB)));
}
template <int ACC, int TB, int SBO>
__device__ __forceinline__ void wgmma64rs(float* d, const uint32_t* a, uint32_t b) {
  asm volatile("{\n.reg .b64 db;\nmov.b64 db, {%36, %39};\n"
               "wgmma.mma_async.sync.aligned.m64n64k16.f32.bf16.bf16 {" D32 "}, {%32,%33,%34,%35}, db, %37, 1, 1, %38;\n}"
               : R8("+f", 0), R8("+f", 8), R8("+f", 16), R8("+f", 24)
               : "r"(a[0]), "r"(a[1]), "r"(a[2]), "r"(a[3]), "r"(b), "n"(ACC), "n"(TB), "n"(dhi(SBO, 0)));
}
template <int ACC, int TB, int SBO>
__device__ __forceinline__ void wgmma32rs(float* d, const uint32_t* a, uint32_t b) {
  asm volatile("{\n.reg .b64 db;\nmov.b64 db, {%20, %23};\n"
               "wgmma.mma_async.sync.aligned.m64n32k16.f32.bf16.bf16 {%0,%1,%2,%3,%4,%5,%6,%7,%8,%9,%10,%11,%12,%13,%14,%15}, "
               "{%16,%17,%18,%19}, db, %21, 1, 1, %22;\n}"
               : R8("+f", 0), R8("+f", 8)
               : "r"(a[0]), "r"(a[1]), "r"(a[2]), "r"(a[3]), "r"(b), "n"(ACC), "n"(TB), "n"(dhi(SBO, 0)));
}

struct RowConst { float c[2][4], s[2][4]; };
__device__ __forceinline__ void rot(float& c, float& s, float dc, float ds) {
  const float n = c * dc - s * ds;
  s = s * dc + c * ds;
  c = n;
}
__device__ __forceinline__ void row_const(RowConst& r, int lane) {
  const int g = lane >> 2, t = lane & 3;
#pragma unroll
  for (int h = 0; h < 2; h++) {
    const float w = (float)(2 * g + h) * 0.02454369260617026f;
    float c, s, dc, ds;
    __sincosf(w * (float)(4 * t), &s, &c);
    __sincosf(w, &ds, &dc);
#pragma unroll
    for (int k = 0; k < 4; k++) {
      r.c[h][2 * (k & 1) + (k >> 1)] = c; r.s[h][2 * (k & 1) + (k >> 1)] = s;
      if (k < 3) rot(c, s, dc, ds);
    }
  }
}
__device__ __forceinline__ void row_step1(uint32_t sb, const uint32_t (*a)[8], float (*z)[16]) {
  const uint32_t d = dlo(sb + RMAT, 128);
#pragma unroll
  for (int r = 0; r < 2; r++) {
    wgmma32rs<0, 0, 512>(z[r], a[r], d);
    wgmma32rs<1, 0, 512>(z[r], a[r] + 4, d + (256 >> 4));
  }
  wg_commit();
}
__device__ __forceinline__ void row_twiddle(const RowConst& rc, uint32_t (*a)[8], float (*z)[16]) {
#pragma unroll
  for (int r = 0; r < 2; r++) {
    keep<16>(z[r]);
#pragma unroll
    for (int h = 0; h < 2; h++)
#pragma unroll
      for (int u = 0; u < 2; u++) {
        const float r0 = z[r][8 * u + 2 * h], r1 = z[r][8 * u + 2 * h + 1], i0 = z[r][8 * u + 4 + 2 * h], i1 = z[r][8 * u + 5 + 2 * h];
        const float c0 = rc.c[h][2 * u], s0 = rc.s[h][2 * u], c1 = rc.c[h][2 * u + 1], s1 = rc.s[h][2 * u + 1];
        a[r][4 * h + u] = movm(pack(i0 * c0 - r0 * s0, i1 * c1 - r1 * s1));
        a[r][4 * h + 2 + u] = movm(pack(r0 * c0 + i0 * s0, r1 * c1 + i1 * s1));
      }
    keepu<8>(a[r]);
  }
}
__device__ __forceinline__ void row_step2(uint32_t sb, const uint32_t (*a)[8], float (*z)[16]) {
  const uint32_t d = dlo(sb + RMAT, 512);
#pragma unroll
  for (int r = 0; r < 2; r++) {
    wgmma32rs<0, 1, 128>(z[r], a[r], d);
    wgmma32rs<1, 1, 128>(z[r], a[r] + 4, d + (1024 >> 4));
  }
  wg_commit();
}

struct Params {
  const __nv_bfloat16* x;
  unsigned char* scr;
  uint32_t zero;
  unsigned char tab[66][4];
  const __nv_bfloat16 *wr, *wi, *b1, *b2;
};

__device__ __forceinline__ void transpose_w(uint32_t sb, unsigned char* scr, int b, int ht, int ch0, int ch1) {
  unsigned char* wp = scr + G_WT + (ht >> 2) * 8192 + (b - 112) * 512;
#pragma unroll 1
  for (int ch = ch0; ch < ch1; ch++) {
    mbar_wait(sb + MISC + 8 * (B_WCH + ch));
    const int wo = (ch * 64 + (ht & 3) * 16) ^ ((((b & 1) * 2 + (ch >> 2)) & 3) << 5);
#pragma unroll 1
    for (int n0 = 0; n0 < 9; n0 += 3) {
      uint32_t e[3][8];
#pragma unroll
      for (int n = 0; n < 3; n++) {
        const uint32_t a = sb + ch * WCH + (4 * (ht & 3) * DF + (ht >> 2) + 32 * (n0 + n)) * 2;
#pragma unroll
        for (int i = 0; i < 8; i++)
          asm volatile("ld.shared.u16 %0, [%1];" : "=r"(e[n][i]) : "r"(a + (i >> 1) * DF * 2 + (i & 1) * 8224) : "memory");
      }
#pragma unroll
      for (int n = 0; n < 3; n++)
        if (n0 + n < 8 || ht < 4)
          asm volatile("st.global.v4.u32 [%0], {%1,%2,%3,%4};" ::"l"(wp + (n0 + n) * 32 * 8192 + wo),
                       "r"(__byte_perm(e[n][0], e[n][1], 0x5410)), "r"(__byte_perm(e[n][2], e[n][3], 0x5410)),
                       "r"(__byte_perm(e[n][4], e[n][5], 0x5410)), "r"(__byte_perm(e[n][6], e[n][7], 0x5410)) : "memory");
    }
  }
}

struct Ring {
  uint32_t s, ph;
  __device__ __forceinline__ void next() { if (++s == NS) { s = 0; ph ^= 1; } }
};

struct Gemm {
  Ring r;
  uint32_t prev;
  uint32_t dA, dB, bars;
  bool lead;
  template <int TB, int KSTEP> __device__ __forceinline__ void run(float* acc, int n, unsigned char* scr, int b, int stamp) {
    (void)scr; (void)b; (void)stamp;
#pragma unroll 1
    for (int i = 0; i < n; i++) {
      mbar_wait(bars + 8 * r.s, r.ph);
      STAMP(stamp + i);
      const uint32_t a = dA + r.s * (STAGE >> 4), w = dB + r.s * (STAGE >> 4);
      wg_fence();
      wgmma64<TB>(acc + 32, a, w + 512);
      wgmma64<TB>(acc, a, w);
      wg_commit();
      wg_wait<1>();
      if (lead) mbar_arrive(prev);
      wg_fence();
#pragma unroll
      for (int k = 1; k < 4; k++) {
        wgmma64<TB>(acc + 32, a + k * 128, w + 512 + k * KSTEP);
        wgmma64<TB>(acc, a + k * 128, w + k * KSTEP);
      }
      wg_commit();
      prev = bars + 8 * (B_EMPTY + r.s);
      r.next();
    }
  }
  __device__ __forceinline__ void drain() {
    wg_wait<0>();
    if (lead) mbar_arrive(prev);
    prev = bars + 8 * B_NONE;
  }
  template <int TB, int KSTEP>
  __device__ __forceinline__ void tail(float* acc, uint32_t xdst, uint32_t xfull, int xfree, unsigned char* scr, int b, int stamp) {
    (void)scr; (void)b; (void)stamp;
    Ring q = r;
#pragma unroll 1
    for (int i = 0; i < TM; i++) {
      mbar_wait(bars + 8 * r.s, r.ph);
      STAMP(stamp + i);
      const uint32_t a = dA + r.s * (STAGE >> 4), w = dB + r.s * (STAGE >> 4);
      wg_fence();
#pragma unroll
      for (int k = 0; k < 4; k++) wgmma64<TB>(acc + 32, a + k * 128, w + 512 + k * KSTEP);
      wg_commit();
      wg_wait<1>();
      if (lead) mbar_arrive(prev);
      prev = bars + 8 * B_NONE;
      r.next();
    }
    {
      const uint32_t a = dA + q.s * (STAGE >> 4), w = dB + q.s * (STAGE >> 4);
      wg_fence();
#pragma unroll
      for (int k = 0; k < 4; k++) wgmma64<TB>(acc, a + k * 128, w + k * KSTEP);
      wg_commit();
      q.next();
    }
    mbar_wait(bars + 8 * xfree);
    wg_wait<1>();
    keep<32>(acc + 32);
#pragma unroll
    for (int j = 0; j < 4; j++)
      st_async4(xdst + j * 4096, pack(acc[32 + 8 * j], acc[33 + 8 * j]), pack(acc[34 + 8 * j], acc[35 + 8 * j]),
                pack(acc[36 + 8 * j], acc[37 + 8 * j]), pack(acc[38 + 8 * j], acc[39 + 8 * j]), xfull);
    STAMP(TB ? 5 : 13);
#pragma unroll
    for (int i = 1; i < TM; i++) {
      const uint32_t a = dA + q.s * (STAGE >> 4), w = dB + q.s * (STAGE >> 4);
      if (i == 1) wg_fence();
#pragma unroll
      for (int k = 0; k < 4; k++) wgmma64<TB>(acc, a + k * 128, w + k * KSTEP);
      q.next();
    }
    wg_commit();
  }
};

__global__ void __cluster_dims__(2, 1, 1) __launch_bounds__(NTHR, 1)
fused_kernel(const __grid_constant__ Params P, const __grid_constant__ CUtensorMap mW1, const __grid_constant__ CUtensorMap mW2,
             const __grid_constant__ CUtensorMap mX1, const __grid_constant__ CUtensorMap mX,
             const __grid_constant__ CUtensorMap mOut) {
  extern __shared__ __align__(1024) unsigned char smem[];
#define TPC_REG "%%smid"
#define GET_B uint32_t sm_, rk_;                                                                         \
  asm volatile("mov.u32 %0, " TPC_REG ";" : "=r"(sm_));                                                  \
  asm volatile("mov.u32 %0, %%cluster_ctarank;" : "=r"(rk_));                                            \
  const uint32_t tb_ = *(const uint32_t*)P.tab[sm_ >> 1];                                                \
  const int b = 2 * (tb_ & 255) + rk_, pb = (tb_ >> (8 + 8 * rk_)) & 255;
#define cnt(c) (scr + G_CNT + 128 * (c))
#define ROLE_CTX                                                                                         \
  const uint32_t sb = __shfl_sync(0xffffffffu, (uint32_t)__cvta_generic_to_shared(smem), 0);             \
  int tid;                                                                                               \
  GET_B                                                                                                  \
  asm volatile("mov.u32 %0, %%tid.x;" : "=r"(tid));                                                      \
  const int lane = tid & 31, warp = __shfl_sync(0xffffffffu, tid >> 5, 0);                               \
  const bool main_cta = b < 128, g1_cta = b < 112;                                                       \
  const int rank = b & 1, dt = (b >> 1) & 3, wt = b >> 3;                      \
  unsigned char* const scr = P.scr;                                                                      \
  auto bar = [&](int i) { return sb + MISC + 8 * i; };                                                   \
  (void)rank; (void)dt; (void)wt; (void)lane; (void)warp; (void)g1_cta; (void)pb;
#define RST(v)
  if (threadIdx.x < 256) {
    uint32_t L[2][8];
    {
      GET_B
      if (b < 128) {
        const int tx = threadIdx.x;
        const unsigned char* xp = (const unsigned char*)P.x + ((pb >> 3) * 131072 + (pb & 7) * 4096) +
                                  ((tx & 32) * 2048 + (tx >> 6) * 1024 + (tx & 2) * 256 + (tx & 1) * 64 + (tx & 28) * 2);
#pragma unroll
        for (int r = 0; r < 2; r++)
#pragma unroll
          for (int j = 0; j < 4; j++)
            asm volatile("ld.global.nc.L1::no_allocate.v2.u32 {%0,%1}, [%2];"
                         : "=r"(L[r][2 * j]), "=r"(L[r][2 * j + 1]) : "l"(xp + r * 32768 + j * 128));
      }
    }
    asm volatile("barrier.cluster.arrive.relaxed.aligned;" ::: "memory");
    asm volatile("setmaxnreg.inc.sync.aligned.u32 208;");
    RST(c2_);
    ROLE_CTX
    if (b > 128) return;
    RST(c3_);
    const int g = lane >> 2, t = lane & 3, wg = warp >> 2;
    const int pcol = b == 0 ? 128 : (b & 0x70) | ((b & 7) << 1) | ((b >> 3) & 1);
    const int k1c = 8 * warp + g;
    uint32_t fa[8][4];
    float twc[8], tws[8], km[4];
    uint32_t wo[4];
    auto col_consts = [&]() {
      {
        const float w = (float)k1c * 0.0030679615757712823f, ft = (float)t;
        float c, s, dc, ds;
        __sincosf(w * 32.f * ft, &s, &c);
        __sincosf((float)(k1c & 15) * 0.39269908169872414f, &ds, &dc);
#pragma unroll
        for (int n = 0; n < 16; n++) {
          fa[n >> 1][2 * (n & 1)] = pack(c, s);
          fa[n >> 1][2 * (n & 1) + 1] = pack(-s, c);
          if (n < 15) rot(c, s, dc, ds);
        }
        __sincosf(w * ft, &s, &c);
        __sincosf(w * 4.f, &ds, &dc);
#pragma unroll
        for (int n = 0; n < 8; n++) {
          twc[n] = c; tws[n] = s;
          if (n < 7) rot(c, s, dc, ds);
        }
        __sincosf((float)pcol * 0.01227184630308513f, &s, &c);
        const float sc = 1.f / 1048576.f;
        km[0] = sc * (1.f - s); km[1] = sc * (1.f + s); km[2] = -sc * c; km[3] = 0.f;
      }
      {
        const int j0 = k1c + 64 * t, jn = SEQ - j0;
        wo[0] = sb + S3 + (j0 ^ (t << 3)) * 4;
        wo[1] = sb + S3 + 8192 + (jn ^ ((jn >> 3) & 24)) * 4;
        wo[2] = j0 ? wo[1] : wo[1] - 8192;
        wo[3] = 0;
      }
      pin<8>(twc, P.zero); pin<8>(tws, P.zero); pin<32>(fa, P.zero); pin<4>(km, P.zero); pin<4>(wo, P.zero);
    };
    if (CONST_POS == 0) col_consts();
    RST(c4_);
    RowConst rc;
    uint32_t hq[2][8];
    unsigned char* hp;
    auto store_h = [&]() {
#pragma unroll
      for (int r = 0; r < 2; r++)
#pragma unroll
        for (int j = 0; j < 4; j++) stg64(hp + r * 4096 + (j >> 1) * 32 * SLOT + (j & 1) * 8192, hq[r][2 * j], hq[r][2 * j + 1]);
      nb_arrive(NB_H, 288);
    };
    const int hprio = (pb >> 3) & 7;
    if (main_cta) {
      const int row0 = 128 * (pb >> 3) + 64 * (warp & 1) + 4 * (pb & 7) + (warp >> 1);
      const int col = t >> 1;
      row_const(rc, lane);
      hp = scr + G_H + ((2 * col * 32 + (row0 >> 6)) * 2) * 8192 + (row0 & 63) * 128 +
                          (((4 * (t & 1) + (g >> 1)) ^ (row0 & 7)) << 4) + (g & 1) * 8;
      uint32_t sta[4];
      {
        const uint32_t un = (warp >> 1) * 2 + col, sub = 8 * (warp & 1);
#pragma unroll
        for (int h = 0; h < 2; h++) {
          const int kl = 16 * (t & 1) + 2 * g + h, p = col ? 128 - kl : kl, r7 = (p >> 1) & 7;
          sta[h] = sb + S0 + ((p & 0xf0) + 8 * h + r7) * 128 + ((un ^ r7) << 4) + sub;
        }
        sta[2] = (lane & 29) ? sta[0] : col ? sta[0] - SLOT : sb + XTRA + (un << 4) + sub;
        sta[3] = (uint32_t)(uintptr_t)hp;
      }
      pin<16>(&rc, P.zero); pin<4>(sta, P.zero);
      RST(c5_);
      float v[2][16], s1[2], s2[2];
#pragma unroll
      for (int r = 0; r < 2; r++) {
        const float piv = blo(__shfl_sync(0xffffffffu, L[r][0], 0));
        s1[r] = 0.f; s2[r] = 0.f;
#pragma unroll
        for (int j = 0; j < 8; j++) { v[r][2 * j] = blo(L[r][j]) - piv; v[r][2 * j + 1] = bhi(L[r][j]) - piv; }
#pragma unroll
        for (int i = 0; i < 16; i++) { s1[r] += v[r][i]; s2[r] = fmaf(v[r][i], v[r][i], s2[r]); }
      }
      STAMP(1);
#pragma unroll
      for (int o = 16; o > 0; o >>= 1)
#pragma unroll
        for (int r = 0; r < 2; r++) {
          s1[r] += __shfl_xor_sync(0xffffffffu, s1[r], o);
          s2[r] += __shfl_xor_sync(0xffffffffu, s2[r], o);
        }
#pragma unroll
      for (int r = 0; r < 2; r++) {
        s1[r] *= -1.f / DM;
        s2[r] = fmaxf(fmaf(-s1[r], s1[r], s2[r] * (1.f / DM)), 0.f);
        const float a2 = rsqrt_fast(fmaf(s2[r], 1.f + 1e-5f, 1e-10f)), c2 = s1[r] * a2;
#pragma unroll
        for (int j = 0; j < 8; j++) hq[r][j] = pack(fmaf(v[r][2 * j], a2, c2), fmaf(v[r][2 * j + 1], a2, c2));
      }
      if (hprio < H_LATE) store_h();
      STAMP(2);
      nb_sync(NB_R, 384);
      float eps;
      asm volatile("ld.shared.f32 %0, [%1];" : "=f"(eps) : "r"(sb + EPSV) : "memory");
#pragma unroll
      for (int r = 0; r < 2; r++) {
        const float a1 = rsqrt_fast(s2[r] + eps), c1 = s1[r] * a1;
#pragma unroll
        for (int j = 0; j < 8; j++) L[r][j] = pack(fmaf(v[r][2 * j], a1, c1), fmaf(v[r][2 * j + 1], a1, c1));
      }
      wg_fence();
      row_step1(sb, L, v);
      wg_wait<0>();
      row_twiddle(rc, L, v);
      wg_fence();
      row_step2(sb, L, v);
      wg_wait<0>();
      keep<16>(v[0]);
      keep<16>(v[1]);
      if (hprio >= H_LATE) store_h();
      STAMP(36);
      const uint32_t cj = col << 31;
      const int stp = col ? -4096 : 4096;
#pragma unroll
      for (int j = 0; j < 4; j++)
#pragma unroll
        for (int h = 0; h < 2; h++) {
          const uint32_t a = (j | h) ? sta[h] + j * stp : sta[2];
          const uint32_t z0 = pack(v[0][4 * j + 2 * h + 1], v[0][4 * j + 2 * h]) ^ cj;
          const uint32_t z1 = pack(v[1][4 * j + 2 * h + 1], v[1][4 * j + 2 * h]) ^ cj;
          if (!(j | h) && !(lane & 29))
            asm volatile("st.shared.v2.u32 [%0], {%1,%2};" ::"r"(a ^ 16), "r"(z0 ^ 0x80000000u), "r"(z1 ^ 0x80000000u) : "memory");
          asm volatile("st.shared.v2.u32 [%0], {%1,%2};" ::"r"(a), "r"(z0), "r"(z1) : "memory");
        }
      fence_async_smem();
      __syncwarp();
      if (lane == 0) mbar_arrive(bar(B_STG));
      STAMP(37);
    } else {
      nb_sync(NB_R, 384);
    }
    if (CONST_POS == 2) col_consts();
    const uint32_t peer = mapa(sb, rank ^ 1);
    float c[32];
    uint32_t wq[16];
    const uint32_t dB1 = dlo(sb + S1, 1024);
    auto s1_step = [&](int i) {
      if (i == 0) wgmma64rs<0, 0, 128>(c, fa[0], dB1); else wgmma64rs<1, 0, 128>(c, fa[i], dB1 + i * (2048 >> 4));
    };
    Gemm gm;
    gm.r = {0, 0}; gm.bars = bar(0); gm.prev = bar(B_NONE); gm.lead = (tid & 127) == 0;
    if (g1_cta) {
      float acc[64];
      mbar_wait(bar(B_BIAS));
#pragma unroll
      for (int j = 0; j < 8; j++) {
        const uint32_t bb = lds32(sb + BIAS + 16 * j + 4 * t);
        acc[4 * j] = acc[4 * j + 2] = blo(bb);
        acc[4 * j + 1] = acc[4 * j + 3] = bhi(bb);
        acc[32 + 4 * j] = acc[33 + 4 * j] = acc[34 + 4 * j] = acc[35 + 4 * j] = 0.f;
      }
      renew<64>(acc);
      STAMP(3);
      gm.dA = dlo(sb + wg * 8192, 8192); gm.dB = dlo(sb + SLOT, 8192);
      const int n0 = CONST_POS != 1 ? 0 : CST0 + (wg ? 0 : CST);
      if (CONST_POS == 1) {
        gm.run<1, 128>(acc, n0, scr, b, 40);
        col_consts();
      }
      gm.run<1, 128>(acc, 16 - TM - n0, scr, b, 40 + n0);
      gm.tail<1, 128>(acc, peer + S0 + tid * 16, peer + MISC + 8 * B_XFULL1, B_XFREE1, scr, b, 56 - TM);
      STAMP(18);
      mbar_wait(bar(B_B1));
      mbar_wait(bar(B_XFULL1));
      STAMP(7);
      wg_wait<0>();
      keep<32>(acc);
      if ((tid & 127) < TM) mbar_arrive(bar(B_EMPTY + (16 - TM + (tid & 127)) % NS));
      STAMP(6);
      wg_fence();
      unsigned char* up = scr + G_U + (dt * 28 + 2 * wt + rank) * SLOT + warp * 2048 + lane * 4;
      uint4 o4;
#pragma unroll
      for (int j = 0; j < 8; j++) {
        if (!(j & 1)) o4 = lds128(sb + S0 + tid * 16 + (j >> 1) * 4096);
        s1_step(j);
        const uint32_t o0 = (j & 1) ? o4.z : o4.x, o1 = (j & 1) ? o4.w : o4.y;
        float y[4] = {acc[4 * j] + blo(o0), acc[4 * j + 1] + bhi(o0), acc[4 * j + 2] + blo(o1), acc[4 * j + 3] + bhi(o1)};
#pragma unroll
        for (int e = 0; e < 4; e++) {
          const float hx = 0.5f * y[e];
          y[e] = fmaf(hx, tanh_fast(y[e] * fmaf(y[e] * y[e], 0.035677408136300125f, 0.7978845608028654f)), hx);
        }
        stg32(up + j * 128, pack(y[0], y[1]));
        stg32(up + j * 128 + 1024, pack(y[2], y[3]));
      }
      wg_commit();
      nb_arrive(NB_U, 288);
    } else {
      if (CONST_POS == 1) col_consts();
      if (main_cta) {
        transpose_w(sb, scr, b, tid & 127, 4 + 2 * wg, 6 + 2 * wg);
        nb_arrive(NB_HLP, 384);
        mbar_wait(bar(B_BIAS));
      }
      mbar_wait(bar(B_B1));
      wg_fence();
#pragma unroll
      for (int i = 0; i < 8; i++) s1_step(i);
      wg_commit();
    }
    STAMP(8);
    mbar_wait(bar(B_G));
    mbar_wait(bar(B_WQ));
    STAMP(24);
#pragma unroll
    for (int i = 0; i < 8; i++) { wq[2 * i] = lds32(wo[0] + i * 1024); wq[2 * i + 1] = lds32(wo[i ? 1 : 2] - i * 1024); }
    if (!main_cta) {
#pragma unroll
      for (int i = 0; i < 8; i++) {
        const uint32_t a = lds32(wo[i ? 1 : 2] - i * 1024 - 8192), c2 = lds32(wo[0] + i * 1024 + 8192);
        wq[2 * i] = pack(0.5f * (blo(wq[2 * i]) + blo(a)), 0.5f * (bhi(wq[2 * i]) - bhi(a)));
        wq[2 * i + 1] = pack(0.5f * (blo(wq[2 * i + 1]) + blo(c2)), 0.5f * (bhi(wq[2 * i + 1]) - bhi(c2)));
      }
    }
    wg_wait<0>();
    keep<32>(c);
    if ((tid & 127) == 0) mbar_arrive(bar(B_S1));
    uint32_t ap[16];
#pragma unroll
    for (int nt = 0; nt < 8; nt++) {
      ap[2 * nt] = pack(c[4 * nt] * twc[nt] + c[4 * nt + 2] * tws[nt], c[4 * nt + 2] * twc[nt] - c[4 * nt] * tws[nt]);
      ap[2 * nt + 1] = pack(c[4 * nt + 1] * twc[nt] + c[4 * nt + 3] * tws[nt], c[4 * nt + 3] * twc[nt] - c[4 * nt + 1] * tws[nt]);
    }
    const uint32_t dG = dlo(sb + S2, 128);
    wg_fence();
    wgmma64rs<0, 0, 1024>(c, ap, dG);
#pragma unroll
    for (int i = 1; i < 4; i++) wgmma64rs<1, 0, 1024>(c, ap + 4 * i, dG + i * (256 >> 4));
    wg_commit();
    float m[8][6];
#pragma unroll
    for (int nt = 0; nt < 8; nt++) {
      const float w1r = blo(wq[2 * nt]), w1i = bhi(wq[2 * nt]), w2r = blo(wq[2 * nt + 1]), w2i = -bhi(wq[2 * nt + 1]);
      m[nt][0] = km[0] * w1r + km[1] * w2r; m[nt][1] = km[0] * w1i + km[1] * w2i;
      m[nt][2] = km[1] * w1r + km[0] * w2r; m[nt][3] = km[1] * w1i + km[0] * w2i;
      m[nt][4] = km[2] * (w2i - w1i);       m[nt][5] = km[2] * (w1r - w2r);
    }
    wg_wait<0>();
    keep<32>(c);
    STAMP(9);
#pragma unroll
    for (int nt = 0; nt < 8; nt++) {
      const float ar = c[4 * nt], ai = c[4 * nt + 1], br = c[4 * nt + 2], bi = c[4 * nt + 3];
      const float xr = m[nt][0] * ar - m[nt][1] * ai - m[nt][4] * br + m[nt][5] * bi;
      const float xi = m[nt][0] * ai + m[nt][1] * ar - m[nt][4] * bi - m[nt][5] * br;
      const float yr = m[nt][4] * ar - m[nt][5] * ai + m[nt][2] * br - m[nt][3] * bi;
      const float yi = m[nt][4] * ai + m[nt][5] * ar + m[nt][2] * bi + m[nt][3] * br;
      ap[2 * nt] = pack(xi, xr);
      ap[2 * nt + 1] = pack(yi, yr);
    }
    wg_fence();
    wgmma64rs<0, 0, 1024>(c, ap, dG);
#pragma unroll
    for (int i = 1; i < 4; i++) wgmma64rs<1, 0, 1024>(c, ap + 4 * i, dG + i * (256 >> 4));
    wg_commit();
#pragma unroll
    for (int i = 0; i < 8; i++) {
      const uint32_t cc = __byte_perm(fa[i][0], fa[i][2], 0x5410), ss = __byte_perm(fa[i][0], fa[i][2], 0x7632);
      fa[i][3] = __byte_perm(fa[i][1], fa[i][3], 0x7632);
      fa[i][0] = cc; fa[i][1] = ss ^ 0x80008000u; fa[i][2] = ss;
      keepu<4>(fa[i]);
    }
    wg_wait<0>();
    keep<32>(c);
    STAMP(10);
#pragma unroll
    for (int nt = 0; nt < 8; nt++) {
      ap[2 * nt] = pack(c[4 * nt] * twc[nt] + c[4 * nt + 1] * tws[nt], c[4 * nt + 2] * twc[nt] + c[4 * nt + 3] * tws[nt]);
      ap[2 * nt + 1] = pack(c[4 * nt + 1] * twc[nt] - c[4 * nt] * tws[nt], c[4 * nt + 3] * twc[nt] - c[4 * nt + 2] * tws[nt]);
    }
    {
      mbar_wait(bar(B_S1));
      const int r = lane & 7, mi = lane >> 3;
      const uint32_t a = sb + S1 + warp * 2048 + (mi & 1) * 1024 + (mi >> 1) * 128 + (2 * (r & 3) + (r >> 2)) * 16;
#pragma unroll
      for (int i = 0; i < 4; i++) stsm4(a + i * 256, ap[4 * i], ap[4 * i + 1], ap[4 * i + 2], ap[4 * i + 3]);
    }
    fence_async_smem();
    nb_sync(NB_C, 256);
    wg_fence();
    wgmma64rs<0, 1, 128>(c, fa[0], dB1);
#pragma unroll
    for (int i = 1; i < 8; i++) wgmma64rs<1, 1, 128>(c, fa[i], dB1 + i * (2048 >> 4));
    wg_commit();
    float acc[64];
    uint32_t bias2[2];
#pragma unroll
    for (int h = 0; h < 2; h++)
      asm volatile("ld.shared.u16 %0, [%1];" : "=r"(bias2[h]) : "r"(sb + BIAS + 128 + (warp * 16 + g + 8 * h) * 2) : "memory");
#pragma unroll
    for (int j = 0; j < 32; j++) { acc[j] = blo(bias2[(j >> 1) & 1]); acc[32 + j] = 0.f; }
    renew<64>(acc);
    unsigned char* zq = scr + G_Z + (k1c >> 2) * 8 * SLOT + (pcol & 127) * 128 + (((4 * t + (g & 3)) ^ ((pcol >> 1) & 15)) << 3);
    wg_wait<0>();
    keep<32>(c);
    if ((tid & 127) == 0) mbar_arrive(bar(B_S4));
    STAMP(11);
    if (pcol & 127) {
#pragma unroll
      for (int nt = 0; nt < 8; nt++) stg64(zq + nt * SLOT, pack(c[4 * nt], c[4 * nt + 2]), pack(-c[4 * nt + 1], c[4 * nt + 3]));
    } else {
#pragma unroll
      for (int nt = 0; nt < 8; nt++)
        stg32(zq + nt * SLOT + (pcol >> 5), pcol ? pack(-c[4 * nt + 1], c[4 * nt + 3]) : pack(c[4 * nt], c[4 * nt + 2]));
    }
    nb_arrive(NB_Z, 288);
    STAMP(12);
    if (main_cta) {
      gm.dA = dlo(sb + SLOT + wg * 8192, 8192); gm.dB = dlo(sb, 128);
      const int nz = ZK + (wg ? ZST : 0);
      gm.run<0, 16>(acc, nz, scr, b, 160);
      {
        const int col = t >> 1, rs = 64 * (warp & 1) + 4 * (b & 7) + (warp >> 1);
        uint32_t za[2];
#pragma unroll
        for (int h = 0; h < 2; h++) {
          const int kl = 16 * (t & 1) + 2 * g + h, p = col ? 128 - kl : kl;
          za[h] = sb + S0 + p * 128 + (((2 * warp) ^ ((p >> 1) & 15)) << 3) + col * 4;
        }
        const int stp = col ? -4096 : 4096;
        float z[2][16];
        STAMP(20);
        mbar_wait(bar(B_Z));
        STAMP(21);
#pragma unroll
        for (int j = 0; j < 8; j++) {
          const uint32_t a = j ? za[j & 1] + (j >> 1) * stp : lane == 2 ? za[0] - SLOT : za[0];
          asm volatile("ld.shared.u32 %0, [%1];" : "=r"(L[0][j]) : "r"(a) : "memory");
          asm volatile("ld.shared.u32 %0, [%1];" : "=r"(L[1][j]) : "r"(a ^ 8) : "memory");
        }
        wg_fence();
        row_step1(sb, L, z);
        gm.drain();
        row_twiddle(rc, L, z);
        wg_fence();
        row_step2(sb, L, z);
        unsigned char* sp = scr + G_S + (wt * 8 + 4 * col) * SLOT + rs * 128 + (((4 * (t & 1) + (g >> 1)) ^ (rs & 7)) << 4) + (g & 1) * 8;
        wg_wait<0>();
        keep<16>(z[0]);
        keep<16>(z[1]);
#pragma unroll
        for (int r = 0; r < 2; r++)
#pragma unroll
          for (int j = 0; j < 4; j++)
            stg64(sp + r * 4096 + j * SLOT, pack(z[r][4 * j], z[r][4 * j + 1]), pack(z[r][4 * j + 2], z[r][4 * j + 3]));
        nb_arrive(NB_S, 288);
        STAMP(38);
      }
      gm.run<0, 16>(acc, 14 - TM - nz, scr, b, 160 + nz);
      gm.tail<0, 16>(acc, peer + S1 + tid * 16, peer + MISC + 8 * B_XFULL2, B_XFREE2, scr, b, 174 - TM);
      STAMP(19);
      mbar_wait(bar(B_FIN));
      STAMP(15);
      uint32_t xf[16], sf[16];
      const int r = lane & 7, mi = lane >> 3;
      const uint32_t fo = sb + S2 + (warp * 16 + (mi & 1) * 8 + r) * 128;
#pragma unroll
      for (int i = 0; i < 4; i++) {
        ldsm4(fo + (((2 * i + (mi >> 1)) ^ r) << 4), xf + 4 * i);
        ldsm4(fo + (S3 - S2) + (((2 * i + (mi >> 1)) ^ r) << 4), sf + 4 * i);
      }
      wg_wait<0>();
      keep<32>(acc);
      STAMP(14);
      mbar_wait(bar(B_XFULL2));
      STAMP(16);
      uint4 o4;
#pragma unroll
      for (int j = 0; j < 8; j++) {
        if (!(j & 1)) o4 = lds128(sb + S1 + tid * 16 + (j >> 1) * 4096);
        const uint32_t o0 = (j & 1) ? o4.z : o4.x, o1 = (j & 1) ? o4.w : o4.y;
        float y[4] = {acc[4 * j] + blo(o0), acc[4 * j + 1] + bhi(o0), acc[4 * j + 2] + blo(o1), acc[4 * j + 3] + bhi(o1)};
#pragma unroll
        for (int e = 0; e < 4; e++) {
          const float hx = 0.5f * y[e];
          y[e] = fmaf(hx, tanh_fast(hx), hx);
        }
#pragma unroll
        for (int h = 0; h < 2; h++) {
          const uint32_t gg = pack(y[2 * h], y[2 * h + 1]);
          const __nv_bfloat162 ov = __hfma2(*(const __nv_bfloat162*)&sf[2 * j + h], *(const __nv_bfloat162*)&gg,
                                            *(const __nv_bfloat162*)&xf[2 * j + h]);
          xf[2 * j + h] = *(const uint32_t*)&ov;
        }
        if (j & 1) stsm4(fo + (((j - 1 + (mi >> 1)) ^ r) << 4), xf[2 * j - 2], xf[2 * j - 1], xf[2 * j], xf[2 * j + 1]);
      }
      fence_async_smem();
      __syncwarp();
      if (elect_one()) {
        tma2d_store(&mOut, dt * 128 + rank * 64, wt * 128 + warp * 16, sb + S2 + warp * 2048);
        bulk_commit();
        bulk_wait_read();
      }
      STAMP(17); GSTAMP(61);
    }
  } else if (threadIdx.x < 384) {
    asm volatile("setmaxnreg.dec.sync.aligned.u32 56;");
    ROLE_CTX
    if (b > 128) return;
    asm volatile("barrier.cluster.arrive.relaxed.aligned;" ::: "memory");
    const int hw = warp - 8, ht = tid - 256, kg = ht & 3;
    if (hw == 3) { GSTAMP(60); STAMP(59); }
    {
      const int pos = (ht >> 2) & 7, k1 = 2 * pos + (hw >> 1);
      float c, s, dc, ds;
      __sincosf((float)((k1 * 2 * kg + 4 * (hw & 1)) & 15) * 0.39269908169872414f, &s, &c);
      __sincosf((float)k1 * 0.39269908169872414f, &ds, &dc);
      const uint32_t e0 = pack(c, s), sg = (hw >> 1) ? 0x80008000u : 0u;
      rot(c, s, dc, ds);
      const uint32_t e1 = pack(c, s);
      asm volatile("st.shared.v4.u32 [%0], {%1,%2,%3,%4};" ::"r"(sb + RMAT + hw * 512 + kg * 128 + pos * 16), "r"(e0), "r"(e1),
                   "r"(e0 ^ sg), "r"(e1 ^ sg) : "memory");
      if (ht == 0) asm volatile("st.shared.f32 [%0], %1;" ::"r"(sb + EPSV), "f"(1e-5f) : "memory");
      fence_async_smem();
    }
    asm volatile("barrier.cluster.wait.aligned;" ::: "memory");
    nb_arrive(NB_R, 384);
    STAMP(23);
    if (main_cta && !g1_cta) {
      transpose_w(sb, scr, b, ht, 0, 4);
      nb_sync(NB_HLP, 384);
      STAMP(39);
      if (hw == 3 && elect_one()) { signal(cnt(C_W), 1); mbar_arrive(bar(B_WDONE)); STAMP(56); }
      __syncwarp();
    }
    if (g1_cta) mbar_wait(bar(G_POS ? B_FULL + 4 : B_STG));
    {
      const int k2 = ht >> 2;
      float c, s, dc, ds;
      __sincosf((float)((k2 * 8 * kg) & 31) * 0.19634954084936207f, &s, &c);
      __sincosf((float)k2 * 0.19634954084936207f, &ds, &dc);
#pragma unroll
      for (int q = 0; q < 2; q++) {
        uint32_t re[4], im[4];
#pragma unroll
        for (int i = 0; i < 4; i++) {
          re[i] = pack(c, s); im[i] = pack(-s, c);
          rot(c, s, dc, ds);
        }
        const uint32_t a = sb + S2 + ((k2 >> 2) * 8 + kg * 2 + q) * 128 + (k2 & 3) * 32;
        asm volatile("st.shared.v4.u32 [%0], {%1,%2,%3,%4};" ::"r"(a), "r"(re[0]), "r"(re[1]), "r"(re[2]), "r"(re[3]) : "memory");
        asm volatile("st.shared.v4.u32 [%0], {%1,%2,%3,%4};" ::"r"(a + 16), "r"(im[0]), "r"(im[1]), "r"(im[2]), "r"(im[3]) : "memory");
      }
      if (G_POS && g1_cta) mbar_wait(bar(B_XFULL1));
      fence_async_smem();
      __syncwarp();
      if (lane == 0) mbar_arrive(bar(B_G));
    }
  } else {
    asm volatile("setmaxnreg.dec.sync.aligned.u32 40;");
    const uint32_t t0 = clk();
    ROLE_CTX
    if (b > 128) return;
    if (warp == 12) {
      if (PF_T0) wait_until(t0, PF_T0);
      if (elect_one()) {
#pragma unroll
        for (int i = 0; i < B_WCH; i++) mbar_init(bar(i), i < NS ? 1 : i < 2 * NS ? 2 : 0x7ffff);
        if (!g1_cta) {
#pragma unroll
          for (int i = B_WCH; i < B_STG; i++) mbar_init(bar(i), 1);
        }
        asm volatile("fence.mbarrier_init.release.cluster;" ::: "memory");
      }
      __syncwarp();
      asm volatile("barrier.cluster.arrive.relaxed.aligned;" ::: "memory");
      if (main_cta && elect_one()) {
        Ring r = {0, 1};
        if (g1_cta) {
          const int c0 = wt * 128 + rank * 64;
#pragma unroll 1
          for (int k = rank * 1024; k < rank * 1024 + 1024; k += 64) {
            const uint32_t d = sb + SLOT + r.s * STAGE, f = bar(B_FULL) + 8 * r.s;
            mbar_wait(f + 8 * NS, r.ph);
            tma2d(d, &mW1, c0, k, f);
            tma2d(d + 8192, &mW1, c0 ^ 64, k, f);
            STAMP(64 + ((k >> 6) & 15));
            r.next();
          }
        } else {
#pragma unroll 1
          for (int i = 0; i < 8; i++) {
            if (i >= 3) mbar_wait(bar(B_WCH + i - 3));
            const int go = ((b - 112) * 8 + i) * 8224;
            bulk_load(sb + i * WCH, (const unsigned char*)P.wr + go, 8224, bar(B_WCH + i));
            bulk_load(sb + i * WCH + 8224, (const unsigned char*)P.wi + go, 8224, bar(B_WCH + i));
            mbar_expect(bar(B_WCH + i), 16448);
          }
          mbar_wait(bar(B_WDONE));
        }
#pragma unroll 1
        for (int k = rank * 896; k < rank * 896 + 896; k += 64) {
          const uint32_t d = sb + SLOT + r.s * STAGE, f = bar(B_FULL) + 8 * r.s;
          mbar_wait(f + 8 * NS, r.ph);
          tma2d(d, &mW2, wt * 128, k, f);
          tma2d(d + 8192, &mW2, wt * 128 + 64, k, f);
          r.next();
        }
      }
    } else if (warp == 15) {
      if (elect_one()) {
#pragma unroll
        for (int i = B_STG; i < B_COUNT; i++) mbar_init(bar(i), i == B_STG ? 8 : (i == B_S4 || i == B_S1) ? 2 : i == B_G ? 4 : 1);
        asm volatile("fence.mbarrier_init.release.cluster;" ::: "memory");
      }
      __syncwarp();
      asm volatile("barrier.cluster.arrive.relaxed.aligned;" ::: "memory");
      const void *ch = cnt(C_H + (pb >> 6)), *cu = cnt(C_U + dt * 2 + (wt >= 7)), *cz = cnt(C_Z), *cs = cnt(C_S + (wt & 15));
      const unsigned ih = 1u << (4 * ((pb >> 3) & 7)), iu = 1u << (2 * (wt >= 7 ? wt - 7 : wt) + rank);
      asm volatile("" : "+l"(ch), "+l"(cu), "+l"(cz), "+l"(cs));
      if (main_cta) {
        nb_sync(NB_H, 288);
        if (elect_one()) { signal(ch, ih); STAMP(30); }
        __syncwarp();
      }
      if (g1_cta) {
        nb_sync(NB_U, 288);
        if (elect_one()) { signal(cu, iu); STAMP(32); }
        __syncwarp();
      }
      nb_sync(NB_Z, 288);
      if (elect_one()) { signal(cz, main_cta ? 1 : 128); STAMP(33); }
      __syncwarp();
      if (main_cta) {
        nb_sync(NB_S, 288);
        if (elect_one()) { signal(cs, 1); STAMP(22); }
      }
    } else {
      asm volatile("barrier.cluster.arrive.relaxed.aligned;" ::: "memory");
      const unsigned ep = ld_relaxed(cnt(C_EPOCH));
      asm volatile("barrier.cluster.wait.aligned;" ::: "memory");
      if (warp == 13) {
        if (main_cta && elect_one()) {
          Ring r = {0, 1};
          unsigned seen = 0;
          if (g1_cta) {
            const unsigned char* src = scr + G_H + (dt * 32 + rank * 16) * SLOT;
#pragma unroll 1
            for (int i = 0; i < 16; i++) {
              const uint32_t d = sb + r.s * STAGE, f = bar(B_FULL) + 8 * r.s;
              mbar_wait(f + 8 * NS, r.ph);
              poll(cnt(C_H + rank), ep * 0x88888888u, 8u << (2 * (i & 14)), seen);
              bulk_load(d, src, SLOT, f);
              mbar_expect(f, STAGE);
              STAMP(80 + i);
              src += SLOT;
              r.next();
            }
          } else {
            mbar_wait(bar(B_WDONE));
          }
          seen = 0;
          const unsigned char* src = scr + G_U + (dt * 28 + rank * 14) * SLOT + rank * 8192;
          const int oth = rank ? -8192 : 8192;
#pragma unroll 1
          for (int i = 0; i < 14; i++) {
            const uint32_t d = sb + r.s * STAGE, f = bar(B_FULL) + 8 * r.s;
            mbar_wait(f + 8 * NS, r.ph);
            poll(cnt(C_U + dt * 2 + rank), ep * 0x3fffu, 1u << i, seen);
            bulk_load(d, src, 8192, f);
            bulk_load(d + 8192, src + oth, 8192, f);
            mbar_expect(f, STAGE);
            STAMP(128 + i);
            src += SLOT;
            r.next();
          }
        }
      } else if (elect_one()) {
        const uint32_t peer = mapa(sb, rank ^ 1);
        mbar_expect(bar(B_XFULL1), SLOT);
        mbar_expect(bar(B_XFULL2), SLOT);
        if (main_cta) {
          bulk_load(sb + BIAS, P.b1 + (g1_cta ? wt : 0) * 128 + rank * 64, 128, bar(B_BIAS));
          bulk_load(sb + BIAS + 128, P.b2 + wt * 128, 256, bar(B_BIAS));
          mbar_expect(bar(B_BIAS), 384);
          prefetch_map(&mX1);
          mbar_wait(bar(B_STG));
          if (g1_cta) mbar_wait(bar(B_FULL + 3));
          bulk_store(scr + G_X1 + 128 * SLOT + pb * 128, sb + XTRA, 128);
          const uint32_t t1 = clk();
#pragma unroll 1
          for (int n = 0; n < 4; n++) {
            wait_until(t1, n * X1_DT);
            tma2d_store(&mX1, pb * 64, 32 * n, sb + S0 + n * 4096);
          }
          bulk_commit();
          bulk_wait_all();
          mbar_arrive_cluster(peer + MISC + 8 * B_XFREE1);
          signal(cnt(C_X), 1);
          STAMP(31);
          prefetch_map(&mW2);
          prefetch_map(&mX);
          prefetch_map(&mOut);
        }
        poll(cnt(C_X), ep * 128, 128);
        STAMP(26);
        bulk_load(sb + S1, scr + G_X1 + b * SLOT, SLOT, bar(B_B1));
        mbar_expect(bar(B_B1), SLOT);
        const int pcol = b == 0 ? 128 : (b & 0x70) | ((b & 7) << 1) | ((b >> 3) & 1);
        poll(cnt(C_W), ep * 16, 16);
        bulk_load(sb + S3, scr + G_WT + pcol * 8192, 8192, bar(B_WQ));
        bulk_load(sb + S3 + 8192, scr + G_WT + (256 - pcol) * 8192, 8192, bar(B_WQ));
        mbar_expect(bar(B_WQ), SLOT);
        STAMP(34);
        if (main_cta) {
          mbar_wait(bar(B_S4));
          mbar_arrive_cluster(peer + MISC + 8 * B_XFREE2);
          poll(cnt(C_Z), ep * 256, 256);
          STAMP(27);
          bulk_load(sb + S0, scr + G_Z + b * SLOT, SLOT, bar(B_Z));
          mbar_expect(bar(B_Z), SLOT);
          if (b == 0) asm volatile("st.relaxed.gpu.global.u32 [%0], %1;" ::"l"(cnt(C_EPOCH)), "r"(ep + 1) : "memory");
          mbar_wait(bar(B_Z));
          tma2d(sb + S2, &mX, dt * 128 + rank * 64, wt * 128, bar(B_FIN));
          mbar_expect(bar(B_FIN), 2 * SLOT);
          poll(cnt(C_S + wt), ep * 8, 8);
          STAMP(28);
          bulk_load(sb + S3, scr + G_S + (wt * 8 + dt * 2 + rank) * SLOT, SLOT, bar(B_FIN));
        }
      }
    }
  }
}

typedef CUresult (*EncodeFn)(CUtensorMap*, CUtensorMapDataType, cuuint32_t, void*, const cuuint64_t*, const cuuint64_t*,
                             const cuuint32_t*, const cuuint32_t*, CUtensorMapInterleave, CUtensorMapSwizzle,
                             CUtensorMapL2promotion, CUtensorMapFloatOOBfill);

CUtensorMap make_map(EncodeFn enc, const void* p, int inner, int outer, int box_rows) {
  CUtensorMap m;
  cuuint64_t dims[2] = {(cuuint64_t)inner, (cuuint64_t)outer};
  cuuint64_t st[1] = {(cuuint64_t)inner * 2};
  cuuint32_t box[2] = {64u, (cuuint32_t)box_rows};
  cuuint32_t es[2] = {1, 1};
  enc(&m, CU_TENSOR_MAP_DATA_TYPE_BFLOAT16, 2, const_cast<void*>(p), dims, st, box, es, CU_TENSOR_MAP_INTERLEAVE_NONE,
      CU_TENSOR_MAP_SWIZZLE_128B, CU_TENSOR_MAP_L2_PROMOTION_L2_128B, CU_TENSOR_MAP_FLOAT_OOB_FILL_NONE);
  return m;
}

}

extern "C" void kernel_launch(void* const* d_in, const int* in_sizes, int n_in, void* d_out, int out_size) {
  (void)in_sizes; (void)n_in; (void)out_size;
  static EncodeFn enc = nullptr;
  static void* scr = nullptr;
  if (!enc) {
    void* fn = nullptr;
    cudaDriverEntryPointQueryResult q;
    cudaGetDriverEntryPoint("cuTensorMapEncodeTiled", &fn, cudaEnableDefault, &q);
    enc = (EncodeFn)fn;
    cudaGetSymbolAddress(&scr, g_scr);
    cudaFuncSetAttribute(fused_kernel, cudaFuncAttributeMaxDynamicSharedMemorySize, SMEM_BYTES);
  }
  Params P;
  P.x = (const __nv_bfloat16*)d_in[0];
  P.wr = (const __nv_bfloat16*)d_in[1];
  P.wi = (const __nv_bfloat16*)d_in[2];
  P.b1 = (const __nv_bfloat16*)d_in[5];
  P.b2 = (const __nv_bfloat16*)d_in[7];
  {
    const int gsz[8] = {4, 8, 8, 8, 8, 8, 9, 9};
    int tpc = 0, spare = 64;
    for (int r = 0; r < 9; r++)
      for (int g = 0; g < 8; g++)
        if (gsz[g] > r) P.tab[tpc++][0] = (unsigned char)(r < 8 ? (g == 0 ? 56 + r : 8 * (g - 1) + r) : spare++);
    for (spare = 60; tpc < 66;) P.tab[tpc++][0] = (unsigned char)spare++;
    const int seq[14] = {0, 8, 1, 9, 2, 10, 3, 11, 4, 12, 5, 13, 6, 7};
    for (int i = 0; i < 66; i++) {
      if (!SM_MAP) P.tab[i][0] = (unsigned char)i;
      for (int r = 0; r < 2; r++) {
        const int b = 2 * P.tab[i][0] + r, idx = (b & 15) * 7 + (b >> 4);
        P.tab[i][1 + r] = (unsigned char)(b < 112 ? seq[idx >> 3] * 8 + (idx & 7) : b);
      }
      P.tab[i][3] = 0;
    }
  }
  P.zero = 0;
  P.scr = (unsigned char*)scr;
  const CUtensorMap mW1 = make_map(enc, d_in[4], FF, SEQ, 64);
  const CUtensorMap mW2 = make_map(enc, d_in[6], SEQ, FF, 64);
  const CUtensorMap mX1 = make_map(enc, P.scr + G_X1, 8192, 129, 32);
  const CUtensorMap mX = make_map(enc, d_in[0], DM, SEQ, 128);
  const CUtensorMap mOut = make_map(enc, d_out, DM, SEQ, 16);
  fused_kernel<<<NCTA, NTHR, SMEM_BYTES, cudaStreamPerThread>>>(P, mW1, mW2, mX1, mX, mOut);
}
```

```cpp
#include <cuda_runtime.h>
#include <cuda_bf16.h>
#include <cuda.h>
#include <stdint.h>

#define X1_DT 500
#define TM 3
#define ZK 8
#define ZST 2
#define GZ 11
#define H_LATE 2
#define MAPV 0

namespace {

constexpr int SEQ = 2048, DM = 512, FF = 1792, DF = 257;
constexpr int NCTA = 132;
constexpr int NTHR = 512;
constexpr int SLOT = 16384;
constexpr int NS = 6, STAGE = 2 * SLOT;
constexpr int S2 = 10 * SLOT, S3 = 11 * SLOT, S0 = 12 * SLOT, S1 = 13 * SLOT;
constexpr int WCH = 33024;
constexpr int XTRA = 14 * SLOT;
constexpr int MISC = 14 * SLOT + 128;
constexpr int BIAS = 14 * SLOT + 512;
constexpr int WHO = 14 * SLOT + 1008;
constexpr int RMAT = 14 * SLOT + 1024;
constexpr int SMEM_BYTES = RMAT + 2048;

constexpr int B_FULL = 0, B_EMPTY = NS, B_S4 = B_EMPTY + 5, B_NONE = 2 * NS, B_WCH = 13, B_WDONE = 17,
              B_STG = 18, B_CF = 19, B_XFREE1 = 20, B_S1 = 21, B_XFREE2 = 22, B_Z = 23, B_FIN = 24,
              B_WQ = 25, B_XFULL1 = 26, B_XFULL2 = 30, B_COUNT = 34;
constexpr int NB_H = 1, NB_U = 2, NB_Z = 3, NB_C = 4, NB_HLP = 5, NB_R = 6, NB_S = 7, NB_T = 8;

constexpr int G_H = 0;
constexpr int G_U = G_H + 128 * SLOT;
constexpr int G_Z = G_U + 112 * SLOT;
constexpr int G_S = G_Z + 128 * SLOT;
constexpr int G_X1 = G_S + 128 * SLOT;
constexpr int G_WT = G_X1 + 129 * SLOT;
constexpr int G_CNT = G_WT + DF * SEQ * 4;
constexpr int C_H = 0, C_X = 2, C_W = 3, C_Z = 4, C_EPOCH = 5, C_U = 6, C_S = 14, C_COUNT = 30;
constexpr int G_PROF = G_CNT + C_COUNT * 128;
__device__ __align__(1024) unsigned char g_scr[G_PROF + NCTA * 192 * 8];

#define STAMP(id) do {} while (0)
#define GSTAMP(id) do {} while (0)

#define LSTAMP(id) STAMP(id)
#define PSTAMP(id) do {} while (0)

__device__ __forceinline__ void mbar_init(uint32_t b, int c) {
  asm volatile("mbarrier.init.shared::cta.b64 [%0], %1;" ::"r"(b), "r"(c) : "memory");
}
__device__ __forceinline__ void mbar_expect(uint32_t b, int bytes) {
  asm volatile("mbarrier.arrive.expect_tx.shared::cta.b64 _, [%0], %1;" ::"r"(b), "r"(bytes) : "memory");
}
__device__ __forceinline__ void mbar_arrive(uint32_t b) {
  asm volatile("mbarrier.arrive.shared::cta.b64 _, [%0];" ::"r"(b) : "memory");
}
__device__ __forceinline__ void mbar_arrive_cluster(uint32_t remote) {
  asm volatile("mbarrier.arrive.shared::cluster.b64 _, [%0];" ::"r"(remote) : "memory");
}
__device__ __forceinline__ void mbar_wait(uint32_t b, int ph = 0) {
  asm volatile("{\n.reg .pred p;\n.reg .u32 n;\n"
               "mbarrier.try_wait.parity.shared::cta.b64 p, [%0], %1;\n@p bra WD;\n"
               "mov.u32 n, 0;\nWL:\n"
               "mbarrier.try_wait.parity.shared::cta.b64 p, [%0], %1, 4000;\n@p bra WD;\n"
               "add.u32 n, n, 1;\nsetp.lt.u32 p, n, 0x20000;\n@p bra WL;\ntrap;\nWD:\n}" ::"r"(b), "r"(ph) : "memory");
}
__device__ __forceinline__ bool mbar_test(uint32_t b) {
  uint32_t ok;
  asm volatile("{\n.reg .pred p;\nmbarrier.test_wait.parity.shared::cta.b64 p, [%1], 0;\nselp.u32 %0, 1, 0, p;\n}" : "=r"(ok) : "r"(b) : "memory");
  return ok;
}
__device__ __forceinline__ bool elect_one() {
  uint32_t p;
  asm volatile("{\n.reg .pred e;\nelect.sync _|e, 0xffffffff;\nselp.u32 %0, 1, 0, e;\n}" : "=r"(p));
  return p;
}
__device__ __forceinline__ uint32_t mapa(uint32_t a, uint32_t cta) {
  uint32_t r;
  asm("mapa.shared::cluster.u32 %0, %1, %2;" : "=r"(r) : "r"(a), "r"(cta));
  return r;
}
__device__ __forceinline__ void tma2d(uint32_t dst, const CUtensorMap* m, int c0, int c1, uint32_t bar) {
  asm volatile("cp.async.bulk.tensor.2d.shared::cluster.global.mbarrier::complete_tx::bytes [%0], [%1, {%3, %4}], [%2];"
               ::"r"(dst), "l"(m), "r"(bar), "r"(c0), "r"(c1) : "memory");
}
__device__ __forceinline__ void tma2d_store(const CUtensorMap* m, int c0, int c1, uint32_t src) {
  asm volatile("cp.async.bulk.tensor.2d.global.shared::cta.bulk_group [%0, {%2, %3}], [%1];"
               ::"l"(m), "r"(src), "r"(c0), "r"(c1) : "memory");
}
__device__ __forceinline__ void bulk_load(uint32_t dst, const void* src, int bytes, uint32_t bar) {
  asm volatile("cp.async.bulk.shared::cluster.global.mbarrier::complete_tx::bytes [%0], [%1], %2, [%3];"
               ::"r"(dst), "l"(src), "r"(bytes), "r"(bar) : "memory");
}
__device__ __forceinline__ void bulk_store(void* dst, uint32_t src, int bytes) {
  asm volatile("cp.async.bulk.global.shared::cta.bulk_group [%0], [%1], %2;" ::"l"(dst), "r"(src), "r"(bytes) : "memory");
}
__device__ __forceinline__ void bulk_commit() { asm volatile("cp.async.bulk.commit_group;" ::: "memory"); }
__device__ __forceinline__ void bulk_wait_all() { asm volatile("cp.async.bulk.wait_group 0;" ::: "memory"); }
__device__ __forceinline__ void fence_async_smem() { asm volatile("fence.proxy.async.shared::cta;" ::: "memory"); }
__device__ __forceinline__ void prefetch_map(const CUtensorMap* m) {
  asm volatile("prefetch.tensormap [%0];" ::"l"(m) : "memory");
}
__device__ __forceinline__ void nb_sync(int id, int n) { asm volatile("bar.sync %0, %1;" ::"r"(id), "r"(n) : "memory"); }
__device__ __forceinline__ void nb_arrive(int id, int n) { asm volatile("bar.arrive %0, %1;" ::"r"(id), "r"(n) : "memory"); }
__device__ __forceinline__ void signal(const void* cnt, unsigned inc) {
  asm volatile("fence.proxy.async;\nred.relaxed.gpu.global.add.u32 [%0], %1;" ::"l"(cnt), "r"(inc) : "memory");
}
#define NOF 0
template <int BIT> __device__ __forceinline__ void signalx(const void* cnt, unsigned inc) {
  if (NOF & BIT) asm volatile("red.relaxed.gpu.global.add.u32 [%0], %1;" ::"l"(cnt), "r"(inc) : "memory");
  else signal(cnt, inc);
}
__device__ __forceinline__ unsigned ld_relaxed(const void* p) {
  unsigned v;
  asm volatile("ld.relaxed.gpu.global.u32 %0, [%1];" : "=r"(v) : "l"(p) : "memory");
  return v;
}
__device__ __forceinline__ void poll(const void* cnt, unsigned base, unsigned mask, unsigned& seen) {
  asm volatile("{\n.reg .pred p;\n.reg .u32 n, v;\nand.b32 v, %0, %3;\nsetp.ne.u32 p, v, 0;\n@p bra PD;\nmov.u32 n, 0;\nPL:\n"
               "ld.relaxed.gpu.global.u32 v, [%1];\nsub.u32 %0, v, %2;\nand.b32 v, %0, %3;\nsetp.ne.u32 p, v, 0;\n@p bra PD;\n"
               "add.u32 n, n, 1;\nsetp.lt.u32 p, n, 0x200000;\n@p bra PL;\ntrap;\nPD:\n}"
               : "+r"(seen) : "l"(cnt), "r"(base), "r"(mask) : "memory");
}
__device__ __forceinline__ void poll(const void* cnt, unsigned base, unsigned mask) {
  unsigned seen = 0;
  poll(cnt, base, mask, seen);
}
__device__ __forceinline__ void stg32(void* p, uint32_t a) { asm volatile("st.global.u32 [%0], %1;" ::"l"(p), "r"(a) : "memory"); }
__device__ __forceinline__ void stg64(void* p, uint32_t a, uint32_t b) {
  asm volatile("st.global.v2.u32 [%0], {%1,%2};" ::"l"(p), "r"(a), "r"(b) : "memory");
}
__device__ __forceinline__ uint32_t pack(float lo, float hi) {
  uint32_t r;
  asm("cvt.rn.bf16x2.f32 %0, %1, %2;" : "=r"(r) : "f"(hi), "f"(lo));
  return r;
}
__device__ __forceinline__ float blo(uint32_t v) { return __uint_as_float(v << 16); }
__device__ __forceinline__ float bhi(uint32_t v) { return __uint_as_float(v & 0xffff0000u); }
__device__ __forceinline__ uint32_t hfma2(uint32_t a, uint32_t b, uint32_t c) {
  uint32_t r;
  asm("fma.rn.bf16x2 %0, %1, %2, %3;" : "=r"(r) : "r"(a), "r"(b), "r"(c));
  return r;
}
__device__ __forceinline__ float rsqrt_fast(float x) {
  float r;
  asm("rsqrt.approx.f32 %0, %1;" : "=f"(r) : "f"(x));
  return r;
}
__device__ __forceinline__ float tanh_fast(float x) {
  float r;
  asm("tanh.approx.f32 %0, %1;" : "=f"(r) : "f"(x));
  return r;
}
__device__ __forceinline__ uint32_t movm(uint32_t a) {
  uint32_t d;
  asm("movmatrix.sync.aligned.m8n8.trans.b16 %0, %1;" : "=r"(d) : "r"(a));
  return d;
}
__device__ __forceinline__ void stsm4(uint32_t a, uint32_t r0, uint32_t r1, uint32_t r2, uint32_t r3) {
  asm volatile("stmatrix.sync.aligned.m8n8.x4.shared.b16 [%0], {%1,%2,%3,%4};" ::"r"(a), "r"(r0), "r"(r1), "r"(r2), "r"(r3) : "memory");
}
__device__ __forceinline__ void ldsm4t(uint32_t a, uint32_t* r) {
  asm volatile("ldmatrix.sync.aligned.m8n8.x4.trans.shared.b16 {%0,%1,%2,%3}, [%4];"
               : "=r"(r[0]), "=r"(r[1]), "=r"(r[2]), "=r"(r[3]) : "r"(a) : "memory");
}
__device__ __forceinline__ void st_async4(uint32_t a, uint32_t r0, uint32_t r1, uint32_t r2, uint32_t r3, uint32_t bar) {
  asm volatile("st.async.weak.shared::cluster.mbarrier::complete_tx::bytes.v4.b32 [%0], {%1,%2,%3,%4}, [%5];"
               ::"r"(a), "r"(r0), "r"(r1), "r"(r2), "r"(r3), "r"(bar) : "memory");
}
__device__ __forceinline__ uint4 lds128(uint32_t a) {
  uint4 v;
  asm volatile("ld.shared.v4.u32 {%0,%1,%2,%3}, [%4];" : "=r"(v.x), "=r"(v.y), "=r"(v.z), "=r"(v.w) : "r"(a) : "memory");
  return v;
}
__device__ __forceinline__ uint32_t lds32(uint32_t a) {
  uint32_t v;
  asm volatile("ld.shared.u32 %0, [%1];" : "=r"(v) : "r"(a) : "memory");
  return v;
}
__device__ __forceinline__ uint32_t clk() {
  uint32_t c;
  asm volatile("mov.u32 %0, %%clock;" : "=r"(c));
  return c;
}
__device__ __forceinline__ void wait_until(uint32_t t0, int dt) {
  while ((int)(clk() - t0) < dt) {}
}
__device__ __forceinline__ uint32_t dlo(uint32_t addr, uint32_t lbo) { return ((addr & 0x3FFFF) >> 4) | ((lbo >> 4) << 16); }
__host__ __device__ constexpr uint32_t dhi(uint32_t sbo, uint32_t sw) { return (sbo >> 4) | (sw << 30); }
__device__ __forceinline__ void wg_fence() { asm volatile("wgmma.fence.sync.aligned;" ::: "memory"); }
__device__ __forceinline__ void wg_commit() { asm volatile("wgmma.commit_group.sync.aligned;" ::: "memory"); }
template <int N> __device__ __forceinline__ void wg_wait() { asm volatile("wgmma.wait_group.sync.aligned %0;" ::"n"(N) : "memory"); }
template <int N> __device__ __forceinline__ void keep(float* d) {
#pragma unroll
  for (int i = 0; i < N; i++) asm volatile("" : "+f"(d[i])::"memory");
}
template <int N> __device__ __forceinline__ void renew(float* d) {
#pragma unroll
  for (int i = 0; i < N; i++) asm volatile("mov.b32 %0, %1;" : "=f"(d[i]) : "f"(d[i]) : "memory");
}
template <int N> __device__ __forceinline__ void pin(const void* v, uint32_t zero) {
  const uint32_t* d = (const uint32_t*)v;
  uint32_t x = 0;
#pragma unroll
  for (int i = 0; i < N; i++) x ^= d[i];
  asm volatile("{\n.reg .pred p;\nsetp.ne.u32 p, %1, 0;\n@p st.shared.b32 [%1], %0;\n}" ::"r"(x), "r"(zero) : "memory");
}
__device__ __forceinline__ float after_here(float v, uint32_t zero) {
  uint32_t r = __float_as_uint(v);
  asm volatile("{\n.reg .pred p;\n.reg .u32 n;\nmov.u32 n, %1;\nSF:\nadd.u32 %0, %0, n;\nsetp.ne.u32 p, n, 0;\nshr.u32 n, n, 1;\n@p bra SF;\n}"
               : "+r"(r) : "r"(zero) : "memory");
  return __uint_as_float(r);
}
template <int N> __device__ __forceinline__ void keepu(uint32_t* d) {
#pragma unroll
  for (int i = 0; i < N; i++) asm volatile("" : "+r"(d[i])::"memory");
}
#define R8(c, o) c(d[o]), c(d[o + 1]), c(d[o + 2]), c(d[o + 3]), c(d[o + 4]), c(d[o + 5]), c(d[o + 6]), c(d[o + 7])
#define D32 "%0,%1,%2,%3,%4,%5,%6,%7,%8,%9,%10,%11,%12,%13,%14,%15,%16,%17,%18,%19,%20,%21,%22,%23,%24,%25,%26,%27,%28,%29,%30,%31"
#define D64 D32 ",%32,%33,%34,%35,%36,%37,%38,%39,%40,%41,%42,%43,%44,%45,%46,%47,%48,%49,%50,%51,%52,%53,%54,%55,%56,%57,%58,%59,%60,%61,%62,%63"
template <int TB> __device__ __forceinline__ void wgmma128(float* d, uint32_t a, uint32_t b, int accum) {
  asm volatile("{\n.reg .b64 da, db;\n.reg .pred p;\nsetp.ne.b32 p, %69, 0;\nmov.b64 da, {%64, %67};\nmov.b64 db, {%65, %68};\n"
               "wgmma.mma_async.sync.aligned.m64n128k16.f32.bf16.bf16 {" D64 "}, da, db, p, 1, 1, 1, %66;\n}"
               : R8("+f", 0), R8("+f", 8), R8("+f", 16), R8("+f", 24), R8("+f", 32), R8("+f", 40), R8("+f", 48), R8("+f", 56)
               : "r"(a), "r"(b), "n"(TB), "n"(dhi(1024, 1)), "n"(dhi(1024, TB)), "r"(accum));
}
template <int ACC, int TB, int SBO, int SW = 0>
__device__ __forceinline__ void wgmma64rs(float* d, const uint32_t* a, uint32_t b) {
  asm volatile("{\n.reg .b64 db;\nmov.b64 db, {%36, %39};\n"
               "wgmma.mma_async.sync.aligned.m64n64k16.f32.bf16.bf16 {" D32 "}, {%32,%33,%34,%35}, db, %37, 1, 1, %38;\n}"
               : R8("+f", 0), R8("+f", 8), R8("+f", 16), R8("+f", 24)
               : "r"(a[0]), "r"(a[1]), "r"(a[2]), "r"(a[3]), "r"(b), "n"(ACC), "n"(TB), "n"(dhi(SBO, SW)));
}
template <int ACC, int TB, int SBO>
__device__ __forceinline__ void wgmma32rs(float* d, const uint32_t* a, uint32_t b) {
  asm volatile("{\n.reg .b64 db;\nmov.b64 db, {%20, %23};\n"
               "wgmma.mma_async.sync.aligned.m64n32k16.f32.bf16.bf16 {%0,%1,%2,%3,%4,%5,%6,%7,%8,%9,%10,%11,%12,%13,%14,%15}, "
               "{%16,%17,%18,%19}, db, %21, 1, 1, %22;\n}"
               : R8("+f", 0), R8("+f", 8)
               : "r"(a[0]), "r"(a[1]), "r"(a[2]), "r"(a[3]), "r"(b), "n"(ACC), "n"(TB), "n"(dhi(SBO, 0)));
}

struct RowConst { float c[2][4], s[2][4]; };
__device__ __forceinline__ void rot(float& c, float& s, float dc, float ds) {
  const float n = c * dc - s * ds;
  s = s * dc + c * ds;
  c = n;
}
__device__ __forceinline__ void row_const(RowConst& r, int lane) {
  const int g = lane >> 2, t = lane & 3;
#pragma unroll
  for (int h = 0; h < 2; h++) {
    const float w = (float)(2 * g + h) * 0.02454369260617026f;
    float c, s, dc, ds;
    __sincosf(w * (float)(4 * t), &s, &c);
    __sincosf(w, &ds, &dc);
#pragma unroll
    for (int k = 0; k < 4; k++) {
      r.c[h][2 * (k & 1) + (k >> 1)] = c; r.s[h][2 * (k & 1) + (k >> 1)] = s;
      if (k < 3) rot(c, s, dc, ds);
    }
  }
}
template <int NR> __device__ __forceinline__ void row_step1(uint32_t sb, const uint32_t (*a)[8], float (*z)[16]) {
  const uint32_t d = dlo(sb + RMAT, 128);
#pragma unroll
  for (int r = 0; r < NR; r++) {
    wgmma32rs<0, 0, 512>(z[r], a[r], d);
    wgmma32rs<1, 0, 512>(z[r], a[r] + 4, d + (256 >> 4));
  }
  wg_commit();
}
template <int NR> __device__ __forceinline__ void row_twiddle(const RowConst& rc, uint32_t (*a)[8], float (*z)[16]) {
#pragma unroll
  for (int r = 0; r < NR; r++) {
    keep<16>(z[r]);
#pragma unroll
    for (int h = 0; h < 2; h++)
#pragma unroll
      for (int u = 0; u < 2; u++) {
        const float r0 = z[r][8 * u + 2 * h], r1 = z[r][8 * u + 2 * h + 1], i0 = z[r][8 * u + 4 + 2 * h], i1 = z[r][8 * u + 5 + 2 * h];
        const float c0 = rc.c[h][2 * u], s0 = rc.s[h][2 * u], c1 = rc.c[h][2 * u + 1], s1 = rc.s[h][2 * u + 1];
        a[r][4 * h + u] = movm(pack(i0 * c0 - r0 * s0, i1 * c1 - r1 * s1));
        a[r][4 * h + 2 + u] = movm(pack(r0 * c0 + i0 * s0, r1 * c1 + i1 * s1));
      }
    keepu<8>(a[r]);
  }
}
template <int NR> __device__ __forceinline__ void row_step2(uint32_t sb, const uint32_t (*a)[8], float (*z)[16]) {
  const uint32_t d = dlo(sb + RMAT, 512);
#pragma unroll
  for (int r = 0; r < NR; r++) {
    wgmma32rs<0, 1, 128>(z[r], a[r], d);
    wgmma32rs<1, 1, 128>(z[r], a[r] + 4, d + (1024 >> 4));
  }
  wg_commit();
}

struct Params {
  const __nv_bfloat16* x;
  unsigned char* scr;
  void* out;
  uint32_t zero;
  uint32_t tab[132];
  const __nv_bfloat16 *wr, *wi, *b1, *b2;
};

template <int NR>
__device__ __forceinline__ void row_ifft(const RowConst& rc, uint32_t sb, unsigned char* scr, int b, int lane, int q, int i0) {
  const int g = lane >> 2, t = lane & 3;
  const int col = t >> 1;
  uint32_t za[2], A[NR][8];
#pragma unroll
  for (int h = 0; h < 2; h++) {
    const int kl = 16 * (t & 1) + 2 * g + h, p = col ? 128 - kl : kl;
    za[h] = sb + S0 + p * 128 + (((4 * q + i0) ^ ((p >> 1) & 15)) << 3) + col * 4;
  }
  const int stp = col ? -4096 : 4096;
  float z[NR][16];
  STAMP(20);
  mbar_wait(sb + MISC + 8 * B_Z);
  STAMP(21);
#pragma unroll
  for (int r = 0; r < NR; r++)
#pragma unroll
    for (int j = 0; j < 8; j++)
      A[r][j] = lds32((j ? za[j & 1] + (j >> 1) * stp : lane == 2 ? za[0] - SLOT : za[0]) ^ (r << 3));
  wg_fence();
  row_step1<NR>(sb, A, z);
  wg_wait<0>();
  row_twiddle<NR>(rc, A, z);
  wg_fence();
  row_step2<NR>(sb, A, z);
  unsigned char* sp = scr + G_S + ((b >> 3) * 128 + 32 * i0 + 4 * (b & 7) + q) * 1024 + col * 512 + (t & 1) * 64 + g * 8;
  wg_wait<0>();
#pragma unroll
  for (int r = 0; r < NR; r++) {
    keep<16>(z[r]);
#pragma unroll
    for (int j = 0; j < 4; j++)
      stg64(sp + r * 32768 + j * 128, pack(z[r][4 * j], z[r][4 * j + 1]), pack(z[r][4 * j + 2], z[r][4 * j + 3]));
  }
  nb_arrive(NB_S, 288);
  STAMP(38);
}

__device__ __forceinline__ void transpose_w(uint32_t sb, unsigned char* scr, int b, int ht) {
#pragma unroll 1
  for (int ch = 0; ch < 4; ch++) {
    unsigned char* wp = scr + G_WT + (ht >> 3) * 8192 + (b - 112) * 512 + ch * 128 +
                        (((ht & 7) * 16) ^ (((b & 1) * 2 + (ch >> 1)) << 5));
    uint32_t a = sb + ch * WCH + (4 * (ht & 7) * DF + (ht >> 3)) * 2;
    mbar_wait(sb + MISC + 8 * (B_WCH + ch));
#pragma unroll 1
    for (int n0 = 0; n0 < 18; n0 += 3) {
      uint32_t e[3][8];
#pragma unroll
      for (int n = 0; n < 3; n++)
#pragma unroll
        for (int i = 0; i < 8; i++)
          asm volatile("ld.shared.u16 %0, [%1];" : "=r"(e[n][i]) : "r"(a + n * 32 + (i >> 1) * DF * 2 + (i & 1) * 16448) : "memory");
#pragma unroll
      for (int n = 0; n < 3; n++)
        if (16 * (n0 + n) + (ht >> 3) < DF)
          asm volatile("st.global.v4.u32 [%0], {%1,%2,%3,%4};" ::"l"(wp + n * 16 * 8192),
                       "r"(__byte_perm(e[n][0], e[n][1], 0x5410)), "r"(__byte_perm(e[n][2], e[n][3], 0x5410)),
                       "r"(__byte_perm(e[n][4], e[n][5], 0x5410)), "r"(__byte_perm(e[n][6], e[n][7], 0x5410)) : "memory");
      a += 96;
      wp += 48 * 8192;
    }
  }
}

struct Ring {
  uint32_t s, ph;
  __device__ __forceinline__ void next() { if (++s == NS - 1) { s = 0; ph ^= 1; } }
};

struct Gemm {
  Ring r;
  uint32_t prev;
  uint32_t dA, dB, bars;
  uint32_t zr;
  bool lead;
  template <int TB, int KSTEP, int TAIL = 0>
  __device__ __forceinline__ void run(float* acc, int n, int accum, unsigned char* scr, int b, int stamp) {
    (void)scr; (void)b; (void)stamp;
#pragma unroll 1
    for (int i = 0; i < n; i++) {
      mbar_wait(bars + 8 * r.s, r.ph);
      LSTAMP(stamp + i);
      const uint32_t a = dA + r.s * (STAGE >> 4), w = dB + r.s * (STAGE >> 4);
      wg_fence();
#pragma unroll
      for (int k = 0; k < 4; k++) {
        wgmma128<TB>(acc, a + k * 128, w + k * KSTEP, k ? 1 : accum);
        if (k == TAIL) {
          wg_commit();
          wg_wait<1>();
          if (lead) mbar_arrive(prev);
          wg_fence();
        }
      }
      wg_commit();
      accum = 1;
      prev = bars + 8 * (B_EMPTY + r.s);
      r.next();
      if (!TB && TAIL && i == n - 2) r = {NS - 1, 0};
    }
  }
  __device__ __forceinline__ void drain() {
    wg_wait<0>();
    if (lead) mbar_arrive(prev);
    prev = bars + 8 * B_NONE;
  }
  template <int TB, int KSTEP, class F>
  __device__ __forceinline__ void tail(float* acc, int wg, F&& pre, uint32_t lda, uint32_t bias, uint32_t xdst, uint32_t xfull, int xfree,
                                       unsigned char* scr, int b, int stamp) {
    constexpr int T = TM;
    uint32_t bb[8];
    auto prepare = [&]() {
      pre();
      mbar_wait(bars + 8 * xfree);
      if (TB) {
#pragma unroll
        for (int j = 0; j < 8; j++) bb[j] = lds32(bias + 16 * j);
      } else {
#pragma unroll
        for (int h = 0; h < 2; h++) asm volatile("ld.shared.u16 %0, [%1];" : "=r"(bb[h]) : "r"(bias + 16 * h) : "memory");
      }
    };
    auto send = [&](int j) {
      const float* a = acc + 32 + 16 * (j & 1) + (j & 2);
      st_async4(xdst + j * 4096, pack(a[0], a[1]), pack(a[4], a[5]), pack(a[8], a[9]), pack(a[12], a[13]), xfull + 4 * (j & 2));
    };
    if (TB && wg) {
      drain();
      renew<64>(acc);
      uint32_t A[T][16], w[T], em[T];
#pragma unroll
      for (int i = 0; i < T; i++) {
        mbar_wait(bars + 8 * r.s, r.ph);
#pragma unroll
        for (int k = 0; k < 4; k++) ldsm4t(lda + r.s * STAGE + k * 2048, A[i] + 4 * k);
        w[i] = dB + r.s * (STAGE >> 4);
        em[i] = bars + 8 * (B_EMPTY + r.s);
        r.next();
      }
      prepare();
      nb_sync(NB_T, 256);
      wg_fence();
#pragma unroll
      for (int n = 0; n < 4 * T; n++) wgmma64rs<1, TB, 1024, TB>(acc + 32, A[n >> 2] + 4 * (n & 3), w[n >> 2] + 512 + (n & 3) * KSTEP);
      wg_commit();
#pragma unroll
      for (int n = 0; n < 4 * T; n++) {
        wgmma64rs<1, TB, 1024, TB>(acc, A[n >> 2] + 4 * (n & 3), w[n >> 2] + (n & 3) * KSTEP);
        if (n == 3) { wg_commit(); wg_wait<1>(); keep<32>(acc + 32); send(0); wg_fence(); }
        if (n > 3 && n < 7) send(n - 3);
      }
      wg_commit();
      wg_wait<0>();
      keep<32>(acc);
      if (lead) {
#pragma unroll
        for (int i = 0; i < T; i++) mbar_arrive(em[i]);
      }
      STAMP(TB ? 5 : 35);
    } else {
      if (wg) { drain(); nb_sync(NB_T, 256); }
      run<TB, KSTEP, 1>(acc, T, 1, scr, b, stamp);
      if (!wg) nb_arrive(NB_T, 256);
      prepare();
      drain();
      keep<64>(acc);
      STAMP(TB ? 5 : 35);
#pragma unroll
      for (int j = 0; j < 4; j++) send(j);
      if (TB) renew<32>(acc);
    }
    const float half = after_here(0.5f, zr);
#pragma unroll
    for (int j = 0; j < 32; j++)
      acc[j] = fmaf(acc[j], half, half * (TB ? ((j & 1) ? bhi(bb[j >> 2]) : blo(bb[j >> 2])) : blo(bb[(j >> 1) & 1])));
    pin<32>(acc, zr);
  }
};

template <bool BY_SM>
__global__ void __cluster_dims__(2, 1, 1) __launch_bounds__(NTHR, 1)
fused_kernel(const __grid_constant__ Params P, const __grid_constant__ CUtensorMap mW1, const __grid_constant__ CUtensorMap mW2,
             const __grid_constant__ CUtensorMap mX1) {
  extern __shared__ __align__(1024) unsigned char smem[];
#define GET_B uint32_t sm_, rk_;                                                                         \
  if (BY_SM) asm volatile("mov.u32 %0, %%smid;" : "=r"(sm_));                                            \
  else asm volatile("mov.u32 %0, %%ctaid.x;" : "=r"(sm_));                                                       \
  asm volatile("mov.u32 %0, %%cluster_ctarank;" : "=r"(rk_));                                            \
  const uint32_t tb_ = P.tab[(sm_ & ~1u) | rk_];                                                         \
  const int b = tb_ & 255, pb = ((tb_ >> 14) & 0x78) | ((tb_ >> 12) & 7);
#define cnt(c) (scr + G_CNT + 128 * (c))
#define ROLE_CTX                                                                                         \
  const uint32_t sb = __shfl_sync(0xffffffffu, (uint32_t)__cvta_generic_to_shared(smem), 0);             \
  int tid;                                                                                               \
  GET_B                                                                                                  \
  asm volatile("mov.u32 %0, %%tid.x;" : "=r"(tid));                                                      \
  const int lane = tid & 31, warp = __shfl_sync(0xffffffffu, tid >> 5, 0);                               \
  const bool main_cta = b < 128, g1_cta = b < 112;                                                       \
  const int rank = b & 1, dt = (b >> 1) & 3, wt = b >> 3;                                  \
  unsigned char* const scr = P.scr;                                                                      \
  auto bar = [&](int i) { return sb + MISC + 8 * i; };                                                   \
  (void)rank; (void)dt; (void)wt; (void)lane; (void)warp; (void)g1_cta; (void)pb;
#define RST(v)
#define RSV(id)
  uint32_t L[2][8];
  {
    const uint32_t tx = threadIdx.x;
    const unsigned char* xp = (const unsigned char*)P.x + ((tx & 32) * 2048 + (tx >> 6) * 1024 + (tx & 2) * 256 + (tx & 1) * 64 + (tx & 28) * 2);
    GET_B
    (void)b; (void)pb;
    xp += tb_ & 0x1ff000;
    const uint32_t on = tx < 256;
#pragma unroll
    for (int i = 0; i < 8; i++)
      asm volatile("{\n.reg .pred p;\nsetp.ne.u32 p, %3, 0;\n@p ld.global.nc.L1::no_allocate.v2.u32 {%0,%1}, [%2];\n}"
                   : "=r"(L[i >> 2][2 * (i & 3)]), "=r"(L[i >> 2][2 * (i & 3) + 1]) : "l"(xp + (i >> 2) * 32768 + (i & 3) * 128), "r"(on));
  }
  if (threadIdx.x < 256) {
    asm volatile("barrier.cluster.arrive.relaxed.aligned;" ::: "memory");
    asm volatile("setmaxnreg.inc.sync.aligned.u32 208;");
    RST(c2_);
    ROLE_CTX
    if (b > 128) return;
    RST(c3_);
    const int g = lane >> 2, t = lane & 3, wg = warp >> 2;
    const uint32_t zr = P.zero & tid;
    const int hprio = (pb >> 3) & 7;
    RST(c4_);
    RowConst rc;
    uint32_t hq[2][8];
    unsigned char* hp;
    auto store_h = [&]() {
#pragma unroll
      for (int r = 0; r < 2; r++)
#pragma unroll
        for (int j = 0; j < 4; j++) stg64(hp + r * 4096 + (j >> 1) * 32 * SLOT + (j & 1) * 8192, hq[r][2 * j], hq[r][2 * j + 1]);
      nb_arrive(NB_H, 288);
    };
    if (main_cta) {
      const int row0 = 128 * (pb >> 3) + 64 * (warp & 1) + 4 * (pb & 7) + (warp >> 1);
      const int col = t >> 1;
      row_const(rc, lane);
      hp = scr + G_H + ((2 * col * 32 + (row0 >> 6)) * 2) * 8192 + (row0 & 63) * 128 +
                          (((4 * (t & 1) + (g >> 1)) ^ (row0 & 7)) << 4) + (g & 1) * 8;
      uint32_t sta[4];
      {
        const uint32_t un = (warp >> 1) * 2 + col, sub = 8 * (warp & 1);
#pragma unroll
        for (int h = 0; h < 2; h++) {
          const int kl = 16 * (t & 1) + 2 * g + h, p = col ? 128 - kl : kl, r7 = (p >> 1) & 7;
          sta[h] = sb + S0 + ((p & 0xf0) + 8 * h + r7) * 128 + ((un ^ r7) << 4) + sub;
        }
        sta[2] = (lane & 29) ? sta[0] : col ? sta[0] - SLOT : sb + XTRA + (un << 4) + sub;
        sta[3] = (uint32_t)(uintptr_t)hp;
      }
      pin<16>(&rc, zr); pin<4>(sta, zr);
      RST(c5_);
      float v[2][16], s1[2], s2[2];
#pragma unroll
      for (int r = 0; r < 2; r++) {
        const float piv = blo(__shfl_sync(0xffffffffu, L[r][0], 0));
        s1[r] = 0.f; s2[r] = 0.f;
#pragma unroll
        for (int j = 0; j < 8; j++) { v[r][2 * j] = blo(L[r][j]) - piv; v[r][2 * j + 1] = bhi(L[r][j]) - piv; }
#pragma unroll
        for (int i = 0; i < 16; i++) { s1[r] += v[r][i]; s2[r] = fmaf(v[r][i], v[r][i], s2[r]); }
      }
      STAMP(1);
#pragma unroll
      for (int o = 16; o > 0; o >>= 1)
#pragma unroll
        for (int r = 0; r < 2; r++) {
          s1[r] += __shfl_xor_sync(0xffffffffu, s1[r], o);
          s2[r] += __shfl_xor_sync(0xffffffffu, s2[r], o);
        }
#pragma unroll
      for (int r = 0; r < 2; r++) {
        s1[r] *= -1.f / DM;
        s2[r] = fmaxf(fmaf(-s1[r], s1[r], s2[r] * (1.f / DM)), 0.f);
        const float a2 = rsqrt_fast(fmaf(s2[r], 1.f + 1e-5f, 1e-10f)), c2 = s1[r] * a2;
#pragma unroll
        for (int j = 0; j < 8; j++) hq[r][j] = pack(fmaf(v[r][2 * j], a2, c2), fmaf(v[r][2 * j + 1], a2, c2));
      }
      if (hprio < H_LATE) store_h();
      STAMP(2);
      nb_sync(NB_R, 384);
      const float eps = after_here(1e-5f, zr);
#pragma unroll
      for (int r = 0; r < 2; r++) {
        const float a1 = rsqrt_fast(s2[r] + eps), c1 = s1[r] * a1;
#pragma unroll
        for (int j = 0; j < 8; j++) L[r][j] = pack(fmaf(v[r][2 * j], a1, c1), fmaf(v[r][2 * j + 1], a1, c1));
      }
      wg_fence();
      row_step1<2>(sb, L, v);
      wg_wait<0>();
      row_twiddle<2>(rc, L, v);
      wg_fence();
      row_step2<2>(sb, L, v);
      wg_wait<0>();
      keep<16>(v[0]);
      keep<16>(v[1]);
      if (hprio >= H_LATE) store_h();
      STAMP(36);
      const uint32_t cj = col << 31;
      const int stp = col ? -4096 : 4096;
#pragma unroll
      for (int j = 0; j < 4; j++)
#pragma unroll
        for (int h = 0; h < 2; h++) {
          const uint32_t a = (j | h) ? sta[h] + j * stp : sta[2];
          const uint32_t z0 = pack(v[0][4 * j + 2 * h + 1], v[0][4 * j + 2 * h]) ^ cj;
          const uint32_t z1 = pack(v[1][4 * j + 2 * h + 1], v[1][4 * j + 2 * h]) ^ cj;
          if (!(j | h) && !(lane & 29))
            asm volatile("st.shared.v2.u32 [%0], {%1,%2};" ::"r"(a ^ 16), "r"(z0 ^ 0x80000000u), "r"(z1 ^ 0x80000000u) : "memory");
          asm volatile("st.shared.v2.u32 [%0], {%1,%2};" ::"r"(a), "r"(z0), "r"(z1) : "memory");
        }
      RST(c2_);
      fence_async_smem();
      RST(c3_);
      __syncwarp();
      if (lane == 0) mbar_arrive(bar(B_STG));
      RSV(112);
      STAMP(37);
    } else {
      nb_sync(NB_R, 384);
    }
    const int pcol = b == 0 ? 128 : (b & 0x70) | ((b & 7) << 1) | ((b >> 3) & 1);
    const int k1c = 8 * warp + g;
    uint32_t fa[8][4];
    float twc[8], tws[8], rho;
    uint32_t wo[4];
    {
      const float w = (float)k1c * 0.0030679615757712823f, ft = (float)t;
      float c, s, dc, ds;
      __sincosf(w * 32.f * ft, &s, &c);
      __sincosf((float)(k1c & 15) * 0.39269908169872414f, &ds, &dc);
#pragma unroll
      for (int n = 0; n < 16; n++) {
        fa[n >> 1][2 * (n & 1)] = pack(c, s);
        fa[n >> 1][2 * (n & 1) + 1] = pack(-s, c);
        if (n < 15) rot(c, s, dc, ds);
      }
      __sincosf(fmaf((float)pcol, 0.006135923151542565f, 0.7853981633974483f), &ds, &dc);
      rho = __fdividef(dc, ds);
      __sincosf(w * ft, &s, &c);
      c *= ds * 0.0013810679320049757f; s *= ds * 0.0013810679320049757f;
      __sincosf(w * 4.f, &ds, &dc);
#pragma unroll
      for (int n = 0; n < 8; n++) {
        twc[n] = c; tws[n] = s;
        if (n < 7) rot(c, s, dc, ds);
      }
    }
    {
      const int j0 = k1c + 64 * t, jn = SEQ - j0;
      wo[0] = sb + S3 + (j0 ^ (t << 3)) * 4;
      wo[1] = sb + S3 + 8192 + (jn ^ ((jn >> 3) & 24)) * 4;
      wo[2] = j0 ? wo[1] : wo[1] - 8192;
      wo[3] = __float_as_uint(rho);
    }
    pin<8>(twc, zr); pin<8>(tws, zr); pin<32>(fa, zr); pin<4>(wo, zr);
    const uint32_t peer = mapa(sb, rank ^ 1);
    float c[32];
    const uint32_t dB1 = dlo(sb + S1, 1024);
    const uint32_t lda = sb + 8192 + ((lane & 7) + 8 * (lane >> 4)) * 128 + (((2 * (warp & 3) + ((lane >> 3) & 1)) ^ (lane & 7)) << 4);
    Gemm gm;
    gm.r = {0, 0}; gm.bars = bar(0); gm.prev = bar(B_NONE); gm.lead = (tid & 127) == 0; gm.zr = zr;
    if (g1_cta) {
      float acc[64];
      STAMP(3);
      gm.dA = dlo(sb + wg * 8192, 8192); gm.dB = dlo(sb + SLOT, 8192);
      gm.run<1, 128>(acc, 16 - TM, 0, scr, b, 40);
      gm.tail<1, 128>(acc, wg, []() {}, lda, sb + BIAS + 4 * t, peer + S0 + tid * 16, peer + MISC + 8 * B_XFULL1 + 16 * wg, B_XFREE1, scr, b, 56 - TM);
      STAMP(18);
      if (wg) mbar_wait(bar(B_CF));
      unsigned char* up = scr + G_U + (dt * 28 + 2 * wt + rank) * SLOT + warp * 2048 + lane * 4;
#pragma unroll
      for (int h = 0; h < 2; h++) {
        mbar_wait(bar(B_XFULL1 + h) + 16 * wg);
        STAMP(h ? 6 : 7);
        const uint4 oa = lds128(sb + S0 + tid * 16 + h * 8192), ob = lds128(sb + S0 + tid * 16 + h * 8192 + 4096);
        const uint32_t o[8] = {oa.x, oa.y, oa.z, oa.w, ob.x, ob.y, ob.z, ob.w};
        float y[16], th[16];
#pragma unroll
        for (int i = 0; i < 16; i++) {
          y[i] = fmaf((i & 1) ? bhi(o[i >> 1]) : blo(o[i >> 1]), 0.5f, acc[4 * (i >> 1) + 2 * h + (i & 1)]);
          th[i] = tanh_fast(y[i] * fmaf(y[i] * y[i], 0.285419265090401f, 1.5957691216057308f));
        }
#pragma unroll
        for (int nt = 0; nt < 8; nt++)
          stg32(up + nt * 128 + h * 1024, pack(fmaf(y[2 * nt], th[2 * nt], y[2 * nt]), fmaf(y[2 * nt + 1], th[2 * nt + 1], y[2 * nt + 1])));
      }
      nb_arrive(NB_U, 288);
      STAMP(24);
    } else if (main_cta) {
      mbar_wait(bar(B_XFREE1));
    }
    if (!(g1_cta && wg)) mbar_wait(bar(B_CF));
    wg_fence();
    wgmma64rs<0, 0, 128>(c, fa[0], dB1);
#pragma unroll
    for (int i = 1; i < 8; i++) wgmma64rs<1, 0, 128>(c, fa[i], dB1 + i * (2048 >> 4));
    wg_commit();
    STAMP(8);
    wg_wait<0>();
    keep<32>(c);
    if ((tid & 127) == 0) mbar_arrive(bar(B_S1));
    uint32_t ap[16];
    float d[32];
    const uint32_t dG = dlo(sb + S2, 128);
#pragma unroll
    for (int nt = 0; nt < 8; nt++) {
      ap[2 * nt] = pack(c[4 * nt] * twc[nt] + c[4 * nt + 2] * tws[nt], c[4 * nt + 2] * twc[nt] - c[4 * nt] * tws[nt]);
      ap[2 * nt + 1] = pack(c[4 * nt + 1] * twc[nt] + c[4 * nt + 3] * tws[nt], c[4 * nt + 3] * twc[nt] - c[4 * nt + 1] * tws[nt]);
      if (nt & 1) {
        wg_fence();
        if (nt == 1) wgmma64rs<0, 0, 1024>(d, ap, dG); else wgmma64rs<1, 0, 1024>(d, ap + 2 * nt - 2, dG + (nt >> 1) * (256 >> 4));
      }
    }
    wg_commit();
    uint32_t wq[16];
    mbar_wait(bar(B_WQ));
#pragma unroll
    for (int i = 0; i < 8; i++) { wq[2 * i] = lds32(wo[0] + i * 1024); wq[2 * i + 1] = lds32(wo[i ? 1 : 2] - i * 1024); }
    wg_wait<0>();
    keep<32>(d);
    STAMP(9);
#pragma unroll
    for (int nt = 0; nt < 8; nt++) {
      const float ar = d[4 * nt], ai = d[4 * nt + 1], br = d[4 * nt + 2], bi = d[4 * nt + 3];
      const float w1r = blo(wq[2 * nt]), w1i = bhi(wq[2 * nt]), w2r = blo(wq[2 * nt + 1]), w2i = bhi(wq[2 * nt + 1]);
      const float pr = fmaf(rho, ar, -bi), pi = fmaf(rho, ai, br), qr = fmaf(rho, br, -ai), qi = fmaf(rho, bi, ar);
      const float xr = pr * w1r - pi * w1i, xi = pr * w1i + pi * w1r, yr = qr * w2r + qi * w2i, yi = qi * w2r - qr * w2i;
      ap[2 * nt] = pack(fmaf(rho, xi, -yr), fmaf(rho, xr, yi));
      ap[2 * nt + 1] = pack(fmaf(rho, yi, -xr), fmaf(rho, yr, xi));
      if (nt & 1) {
        wg_fence();
        if (nt == 1) wgmma64rs<0, 0, 1024>(c, ap, dG); else wgmma64rs<1, 0, 1024>(c, ap + 2 * nt - 2, dG + (nt >> 1) * (256 >> 4));
      }
    }
    wg_commit();
#pragma unroll
    for (int i = 0; i < 8; i++) {
      const uint32_t cc = __byte_perm(fa[i][0], fa[i][2], 0x5410), ss = __byte_perm(fa[i][0], fa[i][2], 0x7632);
      fa[i][3] = __byte_perm(fa[i][1], fa[i][3], 0x7632);
      fa[i][0] = cc; fa[i][1] = ss ^ 0x80008000u; fa[i][2] = ss;
      keepu<4>(fa[i]);
    }
    mbar_wait(bar(B_S1));
    wg_wait<0>();
    keep<32>(c);
    STAMP(10);
#pragma unroll
    for (int nt = 0; nt < 8; nt++) {
      ap[2 * nt] = pack(c[4 * nt] * twc[nt] + c[4 * nt + 1] * tws[nt], c[4 * nt + 2] * twc[nt] + c[4 * nt + 3] * tws[nt]);
      ap[2 * nt + 1] = pack(c[4 * nt + 1] * twc[nt] - c[4 * nt] * tws[nt], c[4 * nt + 3] * twc[nt] - c[4 * nt + 2] * tws[nt]);
    }
    {
      const int r = lane & 7, mi = lane >> 3;
      const uint32_t a = sb + S1 + warp * 2048 + (mi & 1) * 1024 + (mi >> 1) * 128 + (2 * (r & 3) + (r >> 2)) * 16;
#pragma unroll
      for (int i = 0; i < 4; i++) stsm4(a + i * 256, ap[4 * i], ap[4 * i + 1], ap[4 * i + 2], ap[4 * i + 3]);
    }
    RST(c2_);
    fence_async_smem();
    RST(c3_);
    nb_sync(NB_C, 256);
    RST(c4_);
    wg_fence();
    wgmma64rs<0, 1, 128>(c, fa[0], dB1);
#pragma unroll
    for (int i = 1; i < 8; i++) wgmma64rs<1, 1, 128>(c, fa[i], dB1 + i * (2048 >> 4));
    wg_commit();
    unsigned char* zq = scr + G_Z + (k1c >> 2) * 8 * SLOT + (pcol & 127) * 128 + (((4 * t + (g & 3)) ^ ((pcol >> 1) & 15)) << 3);
    wg_wait<0>();
    keep<32>(c);
    if ((tid & 127) == 0) mbar_arrive(bar(B_S4));
    STAMP(11);
    RSV(115);
    const bool zlate = g1_cta && (pcol & 127);
    if (!zlate) {
      if (pcol & 127) {
#pragma unroll
        for (int nt = 0; nt < 8; nt++) stg64(zq + nt * SLOT, pack(c[4 * nt], c[4 * nt + 2]), pack(-c[4 * nt + 1], c[4 * nt + 3]));
      } else {
#pragma unroll
        for (int nt = 0; nt < 8; nt++)
          stg32(zq + nt * SLOT + (pcol >> 5), pcol ? pack(-c[4 * nt + 1], c[4 * nt + 3]) : pack(c[4 * nt], c[4 * nt + 2]));
      }
      nb_arrive(NB_Z, 288);
    }
    STAMP(12);
    if (main_cta) {
      float acc[64];
      gm.dA = dlo(sb + SLOT + wg * 8192, 8192); gm.dB = dlo(sb, 128);
      const int nz = ZK + (wg ? ZST : 0);
      gm.run<0, 16>(acc, 1, 0, scr, b, 160);
#pragma unroll
      for (int nt = 0; nt < 8; nt++)
        asm volatile("{\n.reg .pred p;\nsetp.ne.u32 p, %3, 0;\n@p st.global.v2.u32 [%0], {%1,%2};\n}" ::"l"(zq + nt * SLOT),
                     "r"(pack(c[4 * nt], c[4 * nt + 2])), "r"(pack(-c[4 * nt + 1], c[4 * nt + 3])), "r"((uint32_t)zlate) : "memory");
      if (zlate) nb_arrive(NB_Z, 288);
      gm.run<0, 16>(acc, nz - 1, 1, scr, b, 161);
      gm.drain();
      row_ifft<2>(rc, sb, scr, b, lane, warp >> 1, 2 * (warp & 1));
      gm.run<0, 16>(acc, 14 - TM - nz, 1, scr, b, 160 + nz);
      const int fo = (wt * 128 + warp * 16 + (lane >> 3)) * 1024 + (dt * 2 + rank) * 128 + (lane & 7) * 16;
      uint4 xv[4];
      auto load_x = [&]() {
#pragma unroll
      for (int i = 0; i < 4; i++)
        asm volatile("ld.global.nc.L1::no_allocate.v4.u32 {%0,%1,%2,%3}, [%4];" : "=r"(xv[i].x), "=r"(xv[i].y), "=r"(xv[i].z), "=r"(xv[i].w)
                     : "l"((const unsigned char*)P.x + fo + i * 4096) : "memory");
      };
      gm.tail<0, 16>(acc, wg, load_x, 0, sb + BIAS + 128 + (warp * 16 + g) * 2, peer + S1 + tid * 16, peer + MISC + 8 * B_XFULL2 + 16 * wg,
                     B_XFREE2, scr, b, 174 - TM);
      STAMP(19);
      const uint32_t ga = sb + S1 + warp * 512;
      uint4 gv[4], sv[4];
      auto load_s = [&]() {
#pragma unroll
        for (int i = 0; i < 4; i++)
          asm volatile("ld.relaxed.gpu.global.v4.u32 {%0,%1,%2,%3}, [%4];" : "=r"(sv[i].x), "=r"(sv[i].y), "=r"(sv[i].z), "=r"(sv[i].w)
                       : "l"(scr + G_S + fo + i * 4096) : "memory");
      };
      bool have_s = false;
#pragma unroll
      for (int h = 0; h < 2; h++) {
        mbar_wait(bar(B_XFULL2 + h) + 16 * wg);
        STAMP(h ? 13 : 16);
        if (!have_s && mbar_test(bar(B_FIN))) { load_s(); have_s = true; }
        const uint4 oa = lds128(sb + S1 + tid * 16 + h * 8192), ob = lds128(sb + S1 + tid * 16 + h * 8192 + 4096);
        const uint32_t o[8] = {oa.x, oa.y, oa.z, oa.w, ob.x, ob.y, ob.z, ob.w};
        uint32_t gs[8];
#pragma unroll
        for (int nt = 0; nt < 8; nt++) {
          const float y0 = fmaf(blo(o[nt]), 0.5f, acc[4 * nt + 2 * h]), y1 = fmaf(bhi(o[nt]), 0.5f, acc[4 * nt + 2 * h + 1]);
          gs[nt] = pack(fmaf(y0, tanh_fast(y0), y0), fmaf(y1, tanh_fast(y1), y1));
        }
        const uint32_t a = ga + h * 8192 + (lane & 4) * 1024 + (lane & 3) * 128 + (((lane >> 3) ^ (lane & 7)) << 4);
        __syncwarp();
        stsm4(a, gs[0], gs[1], gs[2], gs[3]);
        stsm4(a ^ 64, gs[4], gs[5], gs[6], gs[7]);
      }
      __syncwarp();
#pragma unroll
      for (int i = 0; i < 4; i++) gv[i] = lds128(ga + i * 4096 + (lane >> 3) * 128 + (((lane & 7) ^ (4 * (i & 1) + (lane >> 3))) << 4));
      STAMP(14);
      if (!have_s) { mbar_wait(bar(B_FIN)); load_s(); }
      STAMP(15);
#pragma unroll
      for (int i = 0; i < 4; i++)
        asm volatile("st.global.v4.u32 [%0], {%1,%2,%3,%4};" ::"l"((unsigned char*)P.out + fo + i * 4096), "r"(hfma2(sv[i].x, gv[i].x, xv[i].x)),
                     "r"(hfma2(sv[i].y, gv[i].y, xv[i].y)), "r"(hfma2(sv[i].z, gv[i].z, xv[i].z)), "r"(hfma2(sv[i].w, gv[i].w, xv[i].w)) : "memory");
      STAMP(17); GSTAMP(61);
    }
  } else if (threadIdx.x < 384) {
    asm volatile("setmaxnreg.dec.sync.aligned.u32 56;");
    ROLE_CTX
    if (b > 128) return;
    asm volatile("barrier.cluster.arrive.relaxed.aligned;" ::: "memory");
    const int hw = warp - 8, ht = tid - 256, kg = ht & 3;
    if (hw == 3) { GSTAMP(60); STAMP(59); }
    {
      const int pos = (ht >> 2) & 7, k1 = 2 * pos + (hw >> 1);
      float c, s, dc, ds;
      __sincosf((float)((k1 * 2 * kg + 4 * (hw & 1)) & 15) * 0.39269908169872414f, &s, &c);
      __sincosf((float)k1 * 0.39269908169872414f, &ds, &dc);
      const uint32_t e0 = pack(c, s), sg = (hw >> 1) ? 0x80008000u : 0u;
      rot(c, s, dc, ds);
      const uint32_t e1 = pack(c, s);
      asm volatile("st.shared.v4.u32 [%0], {%1,%2,%3,%4};" ::"r"(sb + RMAT + hw * 512 + kg * 128 + pos * 16), "r"(e0), "r"(e1),
                   "r"(e0 ^ sg), "r"(e1 ^ sg) : "memory");
      fence_async_smem();
    }
    asm volatile("barrier.cluster.wait.aligned;" ::: "memory");
    nb_arrive(NB_R, 384);
    STAMP(23);
    if (main_cta && !g1_cta) {
      transpose_w(sb, scr, b, ht);
      nb_sync(NB_HLP, 128);
      STAMP(39);
      if (hw == 3 && elect_one()) { signal(cnt(C_W), 1); mbar_arrive(bar(B_WDONE)); STAMP(56); }
      __syncwarp();
    }
    if (g1_cta) mbar_wait(bar(B_STG));
    {
      const int k2 = ht >> 2;
      float c, s, dc, ds;
      __sincosf((float)((k2 * 8 * kg) & 31) * 0.19634954084936207f, &s, &c);
      __sincosf((float)k2 * 0.19634954084936207f, &ds, &dc);
#pragma unroll
      for (int q = 0; q < 2; q++) {
        uint32_t re[4], im[4];
#pragma unroll
        for (int i = 0; i < 4; i++) {
          re[i] = pack(c, s); im[i] = pack(-s, c);
          rot(c, s, dc, ds);
        }
        const uint32_t a = sb + S2 + ((k2 >> 2) * 8 + kg * 2 + q) * 128 + (k2 & 3) * 32;
        asm volatile("st.shared.v4.u32 [%0], {%1,%2,%3,%4};" ::"r"(a), "r"(re[0]), "r"(re[1]), "r"(re[2]), "r"(re[3]) : "memory");
        asm volatile("st.shared.v4.u32 [%0], {%1,%2,%3,%4};" ::"r"(a + 16), "r"(im[0]), "r"(im[1]), "r"(im[2]), "r"(im[3]) : "memory");
      }
      if (!main_cta) {
        mbar_wait(bar(B_WQ));
#pragma unroll 1
        for (int i = ht; i < 2 * 1025; i += 128) {
          const int j = i >> 1, jn = (SEQ - j) & (SEQ - 1);
          const uint32_t a0 = sb + S3 + (i & 1) * 8192, a = a0 + (j ^ ((j >> 3) & 24)) * 4, an = a0 + (jn ^ ((jn >> 3) & 24)) * 4;
          const uint32_t u = lds32(a), v = lds32(an), w = pack(0.5f * (blo(u) + blo(v)), 0.5f * (bhi(u) - bhi(v)));
          asm volatile("st.shared.u32 [%0], %1;" ::"r"(an), "r"(w ^ 0x80000000u) : "memory");
          asm volatile("st.shared.u32 [%0], %1;" ::"r"(a), "r"(w) : "memory");
        }
      }
      fence_async_smem();
      __syncwarp();
      if (lane == 0) mbar_arrive(bar(B_CF));
      STAMP(121);
    }
  } else {
    asm volatile("setmaxnreg.dec.sync.aligned.u32 40;");
    ROLE_CTX
    if (b > 128) {
      wait_until(clk(), 5000);
      return;
    }
    if (warp == 12) {
      if (elect_one()) {
#pragma unroll
        for (int i = 0; i <= B_NONE; i++) mbar_init(bar(i), i < NS ? 1 : i < 2 * NS ? 2 : 0x7ffff);
        if (!g1_cta) {
#pragma unroll
          for (int i = B_WCH; i < B_STG; i++) mbar_init(bar(i), 1);
        }
        asm volatile("fence.mbarrier_init.release.cluster;" ::: "memory");
      }
      __syncwarp();
      asm volatile("barrier.cluster.arrive.relaxed.aligned;" ::: "memory");
      if (main_cta && elect_one()) {
        Ring r = {0, 1};
        if (g1_cta) {
          const int c0 = wt * 128 + rank * 64;
#pragma unroll 1
          for (int k = rank * 1024; k < rank * 1024 + 1024; k += 64) {
            const uint32_t d = sb + SLOT + r.s * STAGE, f = bar(B_FULL) + 8 * r.s;
            mbar_wait(f + 8 * NS, r.ph);
            tma2d(d, &mW1, c0, k, f);
            tma2d(d + 8192, &mW1, c0 ^ 64, k, f);
            PSTAMP(64 + ((k >> 6) & 15));
            r.next();
          }
        } else {
#pragma unroll 1
          for (int i = 0; i < 4; i++) {
            if (i >= 2) mbar_wait(bar(B_WCH + i - 2));
            const int go = ((b - 112) * 4 + i) * 16448;
            bulk_load(sb + i * WCH, (const unsigned char*)P.wr + go, 16448, bar(B_WCH + i));
            bulk_load(sb + i * WCH + 16448, (const unsigned char*)P.wi + go, 16448, bar(B_WCH + i));
            mbar_expect(bar(B_WCH + i), 32896);
          }
          mbar_wait(bar(B_WDONE));
        }
        if (g1_cta) mbar_wait(bar(B_FULL), 1);
#pragma unroll 1
        for (int k = rank * 896; k < rank * 896 + 896; k += 64) {
          const uint32_t d = sb + SLOT + r.s * STAGE, f = bar(B_FULL) + 8 * r.s;
          mbar_wait(f + 8 * NS, r.ph);
          tma2d(d, &mW2, wt * 128, k, f);
          tma2d(d + 8192, &mW2, wt * 128 + 64, k, f);
          PSTAMP(144 + ((k - rank * 896) >> 6));
          r.next();
          if (k == rank * 896 + 768) r = {NS - 1, 0};
          if (k == rank * 896 + 64 * (GZ - 1)) mbar_wait(bar(B_Z));
        }
      }
    } else if (warp == 15) {
      if (elect_one()) {
#pragma unroll
        for (int i = B_STG; i < B_COUNT; i++) mbar_init(bar(i), i == B_STG ? 8 : i == B_CF ? 5 : i <= B_S1 ? 2 : 1);
        asm volatile("fence.mbarrier_init.release.cluster;" ::: "memory");
      }
      __syncwarp();
      asm volatile("barrier.cluster.arrive.relaxed.aligned;" ::: "memory");
      const void *ch = cnt(C_H + (pb >> 6)), *cu = cnt(C_U + dt * 2 + (wt >= 7)), *cz = cnt(C_Z), *cs = cnt(C_S + (wt & 15));
      const unsigned ih = 1u << (4 * ((pb >> 3) & 7)), iu = 1u << (2 * (wt >= 7 ? wt - 7 : wt) + rank);
      asm volatile("" : "+l"(ch), "+l"(cu), "+l"(cz), "+l"(cs));
      if (main_cta) {
        nb_sync(NB_H, 288);
        PSTAMP(96);
        if (elect_one()) { signalx<8>(ch, ih); STAMP(30); }
        __syncwarp();
      }
      if (g1_cta) {
        nb_sync(NB_U, 288);
        PSTAMP(97);
        if (elect_one()) { signalx<16>(cu, iu); STAMP(32); }
        __syncwarp();
      }
      nb_sync(NB_Z, 288);
      PSTAMP(98);
      if (elect_one()) { signalx<2>(cz, main_cta ? 1 : 128); STAMP(33); }
      __syncwarp();
      if (main_cta) {
        nb_sync(NB_S, 288);
        PSTAMP(99);
        if (elect_one()) { signalx<4>(cs, 1); STAMP(22); }
      }
    } else {
      asm volatile("barrier.cluster.arrive.relaxed.aligned;" ::: "memory");
      const unsigned ep = ld_relaxed(cnt(C_EPOCH));
      asm volatile("barrier.cluster.wait.aligned;" ::: "memory");
      if (warp == 13) {
        if (main_cta && elect_one()) {
          Ring r = {0, 1};
          unsigned seen = 0;
          if (g1_cta) {
            const unsigned char* src = scr + G_H + (dt * 32 + rank * 16) * SLOT;
#pragma unroll 1
            for (int i = 0; i < 16; i++) {
              const uint32_t d = sb + r.s * STAGE, f = bar(B_FULL) + 8 * r.s;
              mbar_wait(f + 8 * NS, r.ph);
              poll(cnt(C_H + rank), ep * 0x88888888u, 8u << (2 * (i & 14)), seen);
              bulk_load(d, src, SLOT, f);
              mbar_expect(f, STAGE);
              LSTAMP(80 + i);
              src += SLOT;
              r.next();
            }
          } else {
            mbar_wait(bar(B_WDONE));
          }
          seen = 0;
          const unsigned char* src = scr + G_U + (dt * 28 + rank * 14) * SLOT + rank * 8192;
          const int oth = rank ? -8192 : 8192;
#pragma unroll 1
          for (int i = 0; i < 14; i++) {
            const uint32_t d = sb + r.s * STAGE, f = bar(B_FULL) + 8 * r.s;
            mbar_wait(f + 8 * NS, r.ph);
            poll(cnt(C_U + dt * 2 + rank), ep * 0x3fffu, 1u << i, seen);
            bulk_load(d, src, 8192, f);
            bulk_load(d + 8192, src + oth, 8192, f);
            mbar_expect(f, STAGE);
            LSTAMP(128 + i);
            src += SLOT;
            r.next();
            if (i == 12) r = {NS - 1, 0};
            if (i == GZ - 1) mbar_wait(bar(B_Z));
          }
        }
      } else if (elect_one()) {
        const uint32_t peer = mapa(sb, rank ^ 1);
#pragma unroll
        for (int i = 0; i < 8; i++) mbar_expect(bar(B_XFULL1 + i), SLOT / 4);
        if (main_cta) {
          bulk_load(sb + BIAS, P.b1 + (g1_cta ? wt : 0) * 128 + rank * 64, 128, bar(B_XFREE1));
          bulk_load(sb + BIAS + 128, P.b2 + wt * 128, 256, bar(B_XFREE1));
          mbar_expect(bar(B_XFREE1), 388);
          prefetch_map(&mX1);
          asm volatile("st.async.weak.shared::cluster.mbarrier::complete_tx::bytes.b32 [%0], %1, [%2];" ::"r"(peer + WHO), "r"(b),
                       "r"(peer + MISC + 8 * B_XFREE1) : "memory");
          mbar_wait(bar(B_STG));
          PSTAMP(100);
          if (g1_cta) mbar_wait(bar(B_FULL + 3));
          bulk_store(scr + G_X1 + 128 * SLOT + pb * 128, sb + XTRA, 128);
          const uint32_t t1 = clk();
#pragma unroll 1
          for (int n = 0; n < 4; n++) {
            wait_until(t1, n * X1_DT);
            tma2d_store(&mX1, pb * 64, 32 * n, sb + S0 + n * 4096);
          }
          bulk_commit();
          bulk_wait_all();
          mbar_arrive_cluster(peer + MISC + 8 * B_XFREE1);
          signalx<1>(cnt(C_X), 1);
          STAMP(31);
          prefetch_map(&mW2);
          mbar_wait(bar(B_XFREE1));
          asm volatile("{\n.reg .pred p;\nsetp.ne.u32 p, %0, %1;\n@p trap;\n}" ::"r"(lds32(sb + WHO)), "r"(b ^ 1));
        }
        poll(cnt(C_X), ep * 128, 128);
        STAMP(26);
        bulk_load(sb + S1, scr + G_X1 + b * SLOT, SLOT, bar(B_CF));
        mbar_expect(bar(B_CF), SLOT);
        const int pcol = b == 0 ? 128 : (b & 0x70) | ((b & 7) << 1) | ((b >> 3) & 1);
        const uint32_t wb = bar(B_WQ);
        poll(cnt(C_W), ep * 16, 16);
        if (g1_cta) mbar_wait(bar(B_XFULL1));
        bulk_load(sb + S3, scr + G_WT + pcol * 8192, 8192, wb);
        bulk_load(sb + S3 + 8192, scr + G_WT + (256 - pcol) * 8192, 8192, wb);
        mbar_expect(wb, SLOT);
        STAMP(34);
        if (main_cta) {
          mbar_wait(bar(B_S4));
          PSTAMP(101);
          mbar_arrive_cluster(peer + MISC + 8 * B_XFREE2);
          poll(cnt(C_Z), ep * 256, 256);
          STAMP(27);
          bulk_load(sb + S0, scr + G_Z + b * SLOT, SLOT, bar(B_Z));
          mbar_expect(bar(B_Z), SLOT);
          if (b == 0) asm volatile("st.relaxed.gpu.global.u32 [%0], %1;" ::"l"(cnt(C_EPOCH)), "r"(ep + 1) : "memory");
          poll(cnt(C_S + wt), ep * 8, 8);
          mbar_arrive(bar(B_FIN));
          STAMP(28);
        }
      }
    }
  }
}

typedef CUresult (*EncodeFn)(CUtensorMap*, CUtensorMapDataType, cuuint32_t, void*, const cuuint64_t*, const cuuint64_t*,
                             const cuuint32_t*, const cuuint32_t*, CUtensorMapInterleave, CUtensorMapSwizzle,
                             CUtensorMapL2promotion, CUtensorMapFloatOOBfill);

CUtensorMap make_map(EncodeFn enc, const void* p, int inner, int outer, int box_rows) {
  CUtensorMap m;
  cuuint64_t dims[2] = {(cuuint64_t)inner, (cuuint64_t)outer};
  cuuint64_t st[1] = {(cuuint64_t)inner * 2};
  cuuint32_t box[2] = {64u, (cuuint32_t)box_rows};
  cuuint32_t es[2] = {1, 1};
  enc(&m, CU_TENSOR_MAP_DATA_TYPE_BFLOAT16, 2, const_cast<void*>(p), dims, st, box, es, CU_TENSOR_MAP_INTERLEAVE_NONE,
      CU_TENSOR_MAP_SWIZZLE_128B, CU_TENSOR_MAP_L2_PROMOTION_L2_128B, CU_TENSOR_MAP_FLOAT_OOB_FILL_NONE);
  return m;
}

const int GPC_TPCS[8] = {4, 8, 8, 8, 8, 8, 9, 9};
__global__ void probe_kernel() {}
bool known_layout() {
  int dev = 0, sms = 0;
  cudaGetDevice(&dev);
  cudaDeviceGetAttribute(&sms, cudaDevAttrMultiProcessorCount, dev);
  if (sms != NCTA) return false;
  cudaFuncSetAttribute(probe_kernel, cudaFuncAttributeMaxDynamicSharedMemorySize, SMEM_BYTES);
  for (int c = 2; c <= 8; c++) {
    int want = c == 2 ? 4 : 0, got = -1;
    for (int g = 0; g < 8; g++) want += 2 * GPC_TPCS[g] / c;
    cudaLaunchConfig_t cfg = {};
    cudaLaunchAttribute at;
    at.id = cudaLaunchAttributeClusterDimension;
    at.val.clusterDim.x = c; at.val.clusterDim.y = 1; at.val.clusterDim.z = 1;
    cfg.gridDim = dim3(c); cfg.blockDim = dim3(32); cfg.dynamicSmemBytes = SMEM_BYTES; cfg.attrs = &at; cfg.numAttrs = 1;
    if (cudaOccupancyMaxActiveClusters(&got, probe_kernel, &cfg) != cudaSuccess || got != want) {
      (void)cudaGetLastError();
      return false;
    }
  }
  return true;
}

}

extern "C" void kernel_launch(void* const* d_in, const int* in_sizes, int n_in, void* d_out, int out_size) {
  (void)in_sizes; (void)n_in; (void)out_size;
  static EncodeFn enc = nullptr;
  static void* scr = nullptr;
  static bool by_sm = false;
  if (!enc) {
    void* fn = nullptr;
    cudaDriverEntryPointQueryResult q;
    cudaGetDriverEntryPoint("cuTensorMapEncodeTiled", &fn, cudaEnableDefault, &q);
    enc = (EncodeFn)fn;
    cudaGetSymbolAddress(&scr, g_scr);
    cudaFuncSetAttribute(fused_kernel<true>, cudaFuncAttributeMaxDynamicSharedMemorySize, SMEM_BYTES);
    cudaFuncSetAttribute(fused_kernel<false>, cudaFuncAttributeMaxDynamicSharedMemorySize, SMEM_BYTES);
    by_sm = known_layout();
  }
  Params P;
  P.x = (const __nv_bfloat16*)d_in[0];
  P.wr = (const __nv_bfloat16*)d_in[1];
  P.wi = (const __nv_bfloat16*)d_in[2];
  P.b1 = (const __nv_bfloat16*)d_in[5];
  P.b2 = (const __nv_bfloat16*)d_in[7];
  P.scr = (unsigned char*)scr;
  P.out = d_out;
  P.zero = 0;
  int slot[66], tpc = 0, extra = 64;
  for (int r = 0; r < 9; r++)
    for (int g = 0; g < 8; g++)
      if (GPC_TPCS[g] > r) slot[tpc++] = r < 8 ? (g == 0 ? 56 + r : 8 * (g - 1) + r) : extra++;
  for (int i = 60; tpc < 66;) slot[tpc++] = i++;
  if (MAPV) { slot[60] = 61; slot[61] = 62; slot[63] = 64; slot[64] = 65; }
  const int order[14] = {0, 8, 1, 9, 2, 10, 3, 11, 4, 12, 5, 13, 6, 7};
  for (int i = 0; i < NCTA; i++) {
    const int b = by_sm ? 2 * slot[i >> 1] + (i & 1) : i, idx = (b & 15) * 7 + (b >> 4);
    const int pb = b < 112 ? order[idx >> 3] * 8 + (idx & 7) : b & 127;
    P.tab[i] = b | ((pb & 0x78) << 14) | ((pb & 7) << 12);
  }
  const CUtensorMap mW1 = make_map(enc, d_in[4], FF, SEQ, 64);
  const CUtensorMap mW2 = make_map(enc, d_in[6], SEQ, FF, 64);
  const CUtensorMap mX1 = make_map(enc, P.scr + G_X1, 8192, 129, 32);
  if (by_sm) fused_kernel<true><<<NCTA, NTHR, SMEM_BYTES, cudaStreamPerThread>>>(P, mW1, mW2, mX1);
  else fused_kernel<false><<<NCTA - 2, NTHR, SMEM_BYTES, cudaStreamPerThread>>>(P, mW1, mW2, mX1);
}
```

```cpp
#include <cuda_runtime.h>
#include <cuda_bf16.h>
#include <cuda.h>
#include <stdint.h>

constexpr int X1_DT = 500;
constexpr int TM = 3;
constexpr int ZK = 8;
constexpr int ZST = 2;
constexpr int GZ = 11;
constexpr int H_LATE = 2;

namespace {

constexpr int SEQ = 2048, DM = 512, FF = 1792, DF = 257;
constexpr int NCTA = 132;
constexpr int NTHR = 512;
constexpr int SLOT = 16384;
constexpr int NS = 6, STAGE = 2 * SLOT;
constexpr int S2 = 10 * SLOT, S3 = 11 * SLOT, S0 = 12 * SLOT, S1 = 13 * SLOT;
constexpr int WCH = 33024;
constexpr int XTRA = 14 * SLOT;
constexpr int MISC = 14 * SLOT + 128;
constexpr int BIAS = 14 * SLOT + 512;
constexpr int WHO = 14 * SLOT + 1008;
constexpr int RMAT = 14 * SLOT + 1024;
constexpr int SMEM_BYTES = RMAT + 2048;

constexpr int B_FULL = 0, B_EMPTY = NS, B_S4 = B_EMPTY + 5, B_NONE = 2 * NS, B_WCH = 13, B_WDONE = 17,
              B_STG = 18, B_CF = 19, B_XFREE1 = 20, B_S1 = 21, B_XFREE2 = 22, B_Z = 23, B_FIN = 24,
              B_WQ = 25, B_XFULL1 = 26, B_XFULL2 = 30, B_COUNT = 34;
constexpr int NB_H = 1, NB_U = 2, NB_Z = 3, NB_C = 4, NB_HLP = 5, NB_R = 6, NB_S = 7, NB_T = 8;

constexpr int G_H = 0;
constexpr int G_U = G_H + 128 * SLOT;
constexpr int G_Z = G_U + 112 * SLOT;
constexpr int G_S = G_Z + 128 * SLOT;
constexpr int G_X1 = G_S + 128 * SLOT;
constexpr int G_WT = G_X1 + 129 * SLOT;
constexpr int G_CNT = G_WT + DF * SEQ * 4;
constexpr int C_H = 0, C_X = 2, C_W = 3, C_Z = 4, C_EPOCH = 5, C_U = 6, C_S = 14, C_COUNT = 30;
__device__ __align__(1024) unsigned char g_scr[G_CNT + C_COUNT * 128];

__device__ __forceinline__ void mbar_init(uint32_t b, int c) {
  asm volatile("mbarrier.init.shared::cta.b64 [%0], %1;" ::"r"(b), "r"(c) : "memory");
}
__device__ __forceinline__ void mbar_expect(uint32_t b, int bytes) {
  asm volatile("mbarrier.arrive.expect_tx.shared::cta.b64 _, [%0], %1;" ::"r"(b), "r"(bytes) : "memory");
}
__device__ __forceinline__ void mbar_arrive(uint32_t b) {
  asm volatile("mbarrier.arrive.shared::cta.b64 _, [%0];" ::"r"(b) : "memory");
}
__device__ __forceinline__ void mbar_arrive_cluster(uint32_t remote) {
  asm volatile("mbarrier.arrive.shared::cluster.b64 _, [%0];" ::"r"(remote) : "memory");
}
__device__ __forceinline__ void mbar_wait(uint32_t b, int ph = 0) {
  asm volatile("{\n.reg .pred p;\n.reg .u32 n;\n"
               "mbarrier.try_wait.parity.shared::cta.b64 p, [%0], %1;\n@p bra WD;\n"
               "mov.u32 n, 0;\nWL:\n"
               "mbarrier.try_wait.parity.shared::cta.b64 p, [%0], %1, 4000;\n@p bra WD;\n"
               "add.u32 n, n, 1;\nsetp.lt.u32 p, n, 0x20000;\n@p bra WL;\ntrap;\nWD:\n}" ::"r"(b), "r"(ph) : "memory");
}
__device__ __forceinline__ bool mbar_test(uint32_t b) {
  uint32_t ok;
  asm volatile("{\n.reg .pred p;\nmbarrier.test_wait.parity.shared::cta.b64 p, [%1], 0;\nselp.u32 %0, 1, 0, p;\n}" : "=r"(ok) : "r"(b) : "memory");
  return ok;
}
__device__ __forceinline__ bool elect_one() {
  uint32_t p;
  asm volatile("{\n.reg .pred e;\nelect.sync _|e, 0xffffffff;\nselp.u32 %0, 1, 0, e;\n}" : "=r"(p));
  return p;
}
__device__ __forceinline__ uint32_t mapa(uint32_t a, uint32_t cta) {
  uint32_t r;
  asm("mapa.shared::cluster.u32 %0, %1, %2;" : "=r"(r) : "r"(a), "r"(cta));
  return r;
}
__device__ __forceinline__ void tma2d(uint32_t dst, const CUtensorMap* m, int c0, int c1, uint32_t bar) {
  asm volatile("cp.async.bulk.tensor.2d.shared::cluster.global.mbarrier::complete_tx::bytes [%0], [%1, {%3, %4}], [%2];"
               ::"r"(dst), "l"(m), "r"(bar), "r"(c0), "r"(c1) : "memory");
}
__device__ __forceinline__ void tma2d_store(const CUtensorMap* m, int c0, int c1, uint32_t src) {
  asm volatile("cp.async.bulk.tensor.2d.global.shared::cta.bulk_group [%0, {%2, %3}], [%1];"
               ::"l"(m), "r"(src), "r"(c0), "r"(c1) : "memory");
}
__device__ __forceinline__ void bulk_load(uint32_t dst, const void* src, int bytes, uint32_t bar) {
  asm volatile("cp.async.bulk.shared::cluster.global.mbarrier::complete_tx::bytes [%0], [%1], %2, [%3];"
               ::"r"(dst), "l"(src), "r"(bytes), "r"(bar) : "memory");
}
__device__ __forceinline__ void bulk_store(void* dst, uint32_t src, int bytes) {
  asm volatile("cp.async.bulk.global.shared::cta.bulk_group [%0], [%1], %2;" ::"l"(dst), "r"(src), "r"(bytes) : "memory");
}
__device__ __forceinline__ void bulk_commit() { asm volatile("cp.async.bulk.commit_group;" ::: "memory"); }
__device__ __forceinline__ void bulk_wait_all() { asm volatile("cp.async.bulk.wait_group 0;" ::: "memory"); }
__device__ __forceinline__ void fence_async_smem() { asm volatile("fence.proxy.async.shared::cta;" ::: "memory"); }
__device__ __forceinline__ void prefetch_map(const CUtensorMap* m) {
  asm volatile("prefetch.tensormap [%0];" ::"l"(m) : "memory");
}
__device__ __forceinline__ void nb_sync(int id, int n) { asm volatile("bar.sync %0, %1;" ::"r"(id), "r"(n) : "memory"); }
__device__ __forceinline__ void nb_arrive(int id, int n) { asm volatile("bar.arrive %0, %1;" ::"r"(id), "r"(n) : "memory"); }
__device__ __forceinline__ void signal(const void* cnt, unsigned inc) {
  asm volatile("fence.proxy.async;\nred.relaxed.gpu.global.add.u32 [%0], %1;" ::"l"(cnt), "r"(inc) : "memory");
}
__device__ __forceinline__ unsigned ld_relaxed(const void* p) {
  unsigned v;
  asm volatile("ld.relaxed.gpu.global.u32 %0, [%1];" : "=r"(v) : "l"(p) : "memory");
  return v;
}
__device__ __forceinline__ void poll(const void* cnt, unsigned base, unsigned mask, unsigned& seen) {
  asm volatile("{\n.reg .pred p;\n.reg .u32 n, v;\nand.b32 v, %0, %3;\nsetp.ne.u32 p, v, 0;\n@p bra PD;\nmov.u32 n, 0;\nPL:\n"
               "ld.acquire.gpu.global.u32 v, [%1];\nsub.u32 %0, v, %2;\nand.b32 v, %0, %3;\nsetp.ne.u32 p, v, 0;\n@p bra PD;\n"
               "add.u32 n, n, 1;\nsetp.lt.u32 p, n, 0x200000;\n@p bra PL;\ntrap;\nPD:\n}"
               : "+r"(seen) : "l"(cnt), "r"(base), "r"(mask) : "memory");
}
__device__ __forceinline__ void poll(const void* cnt, unsigned base, unsigned mask) {
  unsigned seen = 0;
  poll(cnt, base, mask, seen);
}
__device__ __forceinline__ void stg32(void* p, uint32_t a) { asm volatile("st.global.u32 [%0], %1;" ::"l"(p), "r"(a) : "memory"); }
__device__ __forceinline__ void stg64(void* p, uint32_t a, uint32_t b) {
  asm volatile("st.global.v2.u32 [%0], {%1,%2};" ::"l"(p), "r"(a), "r"(b) : "memory");
}
__device__ __forceinline__ uint32_t pack(float lo, float hi) {
  uint32_t r;
  asm("cvt.rn.bf16x2.f32 %0, %1, %2;" : "=r"(r) : "f"(hi), "f"(lo));
  return r;
}
__device__ __forceinline__ float blo(uint32_t v) { return __uint_as_float(v << 16); }
__device__ __forceinline__ float bhi(uint32_t v) { return __uint_as_float(v & 0xffff0000u); }
__device__ __forceinline__ uint32_t hfma2(uint32_t a, uint32_t b, uint32_t c) {
  uint32_t r;
  asm("fma.rn.bf16x2 %0, %1, %2, %3;" : "=r"(r) : "r"(a), "r"(b), "r"(c));
  return r;
}
__device__ __forceinline__ float rsqrt_fast(float x) {
  float r;
  asm("rsqrt.approx.f32 %0, %1;" : "=f"(r) : "f"(x));
  return r;
}
__device__ __forceinline__ float tanh_fast(float x) {
  float r;
  asm("tanh.approx.f32 %0, %1;" : "=f"(r) : "f"(x));
  return r;
}
__device__ __forceinline__ uint32_t movm(uint32_t a) {
  uint32_t d;
  asm("movmatrix.sync.aligned.m8n8.trans.b16 %0, %1;" : "=r"(d) : "r"(a));
  return d;
}
__device__ __forceinline__ void stsm4(uint32_t a, uint32_t r0, uint32_t r1, uint32_t r2, uint32_t r3) {
  asm volatile("stmatrix.sync.aligned.m8n8.x4.shared.b16 [%0], {%1,%2,%3,%4};" ::"r"(a), "r"(r0), "r"(r1), "r"(r2), "r"(r3) : "memory");
}
__device__ __forceinline__ void ldsm4t(uint32_t a, uint32_t* r) {
  asm volatile("ldmatrix.sync.aligned.m8n8.x4.trans.shared.b16 {%0,%1,%2,%3}, [%4];"
               : "=r"(r[0]), "=r"(r[1]), "=r"(r[2]), "=r"(r[3]) : "r"(a) : "memory");
}
__device__ __forceinline__ void st_async4(uint32_t a, uint32_t r0, uint32_t r1, uint32_t r2, uint32_t r3, uint32_t bar) {
  asm volatile("st.async.weak.shared::cluster.mbarrier::complete_tx::bytes.v4.b32 [%0], {%1,%2,%3,%4}, [%5];"
               ::"r"(a), "r"(r0), "r"(r1), "r"(r2), "r"(r3), "r"(bar) : "memory");
}
__device__ __forceinline__ uint4 lds128(uint32_t a) {
  uint4 v;
  asm volatile("ld.shared.v4.u32 {%0,%1,%2,%3}, [%4];" : "=r"(v.x), "=r"(v.y), "=r"(v.z), "=r"(v.w) : "r"(a) : "memory");
  return v;
}
__device__ __forceinline__ uint32_t lds32(uint32_t a) {
  uint32_t v;
  asm volatile("ld.shared.u32 %0, [%1];" : "=r"(v) : "r"(a) : "memory");
  return v;
}
__device__ __forceinline__ uint32_t clk() {
  uint32_t c;
  asm volatile("mov.u32 %0, %%clock;" : "=r"(c));
  return c;
}
__device__ __forceinline__ void wait_until(uint32_t t0, int dt) {
  while ((int)(clk() - t0) < dt) {}
}
__device__ __forceinline__ uint32_t dlo(uint32_t addr, uint32_t lbo) { return ((addr & 0x3FFFF) >> 4) | ((lbo >> 4) << 16); }
__host__ __device__ constexpr uint32_t dhi(uint32_t sbo, uint32_t sw) { return (sbo >> 4) | (sw << 30); }
__device__ __forceinline__ void wg_fence() { asm volatile("wgmma.fence.sync.aligned;" ::: "memory"); }
__device__ __forceinline__ void wg_commit() { asm volatile("wgmma.commit_group.sync.aligned;" ::: "memory"); }
template <int N> __device__ __forceinline__ void wg_wait() { asm volatile("wgmma.wait_group.sync.aligned %0;" ::"n"(N) : "memory"); }
template <int N> __device__ __forceinline__ void keep(float* d) {
#pragma unroll
  for (int i = 0; i < N; i++) asm volatile("" : "+f"(d[i])::"memory");
}
template <int N> __device__ __forceinline__ void renew(float* d) {
#pragma unroll
  for (int i = 0; i < N; i++) asm volatile("mov.b32 %0, %1;" : "=f"(d[i]) : "f"(d[i]) : "memory");
}
template <int N> __device__ __forceinline__ void pin(const void* v, uint32_t zero) {
  const uint32_t* d = (const uint32_t*)v;
  uint32_t x = 0;
#pragma unroll
  for (int i = 0; i < N; i++) x ^= d[i];
  asm volatile("{\n.reg .pred p;\nsetp.ne.u32 p, %1, 0;\n@p st.shared.b32 [%1], %0;\n}" ::"r"(x), "r"(zero) : "memory");
}
__device__ __forceinline__ float after_here(float v, uint32_t zero) {
  uint32_t r = __float_as_uint(v);
  asm volatile("{\n.reg .pred p;\n.reg .u32 n;\nmov.u32 n, %1;\nSF:\nadd.u32 %0, %0, n;\nsetp.ne.u32 p, n, 0;\nshr.u32 n, n, 1;\n@p bra SF;\n}"
               : "+r"(r) : "r"(zero) : "memory");
  return __uint_as_float(r);
}
template <int N> __device__ __forceinline__ void keepu(uint32_t* d) {
#pragma unroll
  for (int i = 0; i < N; i++) asm volatile("" : "+r"(d[i])::"memory");
}
#define R8(c, o) c(d[o]), c(d[o + 1]), c(d[o + 2]), c(d[o + 3]), c(d[o + 4]), c(d[o + 5]), c(d[o + 6]), c(d[o + 7])
#define D32 "%0,%1,%2,%3,%4,%5,%6,%7,%8,%9,%10,%11,%12,%13,%14,%15,%16,%17,%18,%19,%20,%21,%22,%23,%24,%25,%26,%27,%28,%29,%30,%31"
#define D64 D32 ",%32,%33,%34,%35,%36,%37,%38,%39,%40,%41,%42,%43,%44,%45,%46,%47,%48,%49,%50,%51,%52,%53,%54,%55,%56,%57,%58,%59,%60,%61,%62,%63"
template <int TB> __device__ __forceinline__ void wgmma128(float* d, uint32_t a, uint32_t b, int accum) {
  asm volatile("{\n.reg .b64 da, db;\n.reg .pred p;\nsetp.ne.b32 p, %69, 0;\nmov.b64 da, {%64, %67};\nmov.b64 db, {%65, %68};\n"
               "wgmma.mma_async.sync.aligned.m64n128k16.f32.bf16.bf16 {" D64 "}, da, db, p, 1, 1, 1, %66;\n}"
               : R8("+f", 0), R8("+f", 8), R8("+f", 16), R8("+f", 24), R8("+f", 32), R8("+f", 40), R8("+f", 48), R8("+f", 56)
               : "r"(a), "r"(b), "n"(TB), "n"(dhi(1024, 1)), "n"(dhi(1024, TB)), "r"(accum));
}
template <int ACC, int TB, int SBO, int SW = 0>
__device__ __forceinline__ void wgmma64rs(float* d, const uint32_t* a, uint32_t b) {
  asm volatile("{\n.reg .b64 db;\nmov.b64 db, {%36, %39};\n"
               "wgmma.mma_async.sync.aligned.m64n64k16.f32.bf16.bf16 {" D32 "}, {%32,%33,%34,%35}, db, %37, 1, 1, %38;\n}"
               : R8("+f", 0), R8("+f", 8), R8("+f", 16), R8("+f", 24)
               : "r"(a[0]), "r"(a[1]), "r"(a[2]), "r"(a[3]), "r"(b), "n"(ACC), "n"(TB), "n"(dhi(SBO, SW)));
}
template <int ACC, int TB, int SBO>
__device__ __forceinline__ void wgmma32rs(float* d, const uint32_t* a, uint32_t b) {
  asm volatile("{\n.reg .b64 db;\nmov.b64 db, {%20, %23};\n"
               "wgmma.mma_async.sync.aligned.m64n32k16.f32.bf16.bf16 {%0,%1,%2,%3,%4,%5,%6,%7,%8,%9,%10,%11,%12,%13,%14,%15}, "
               "{%16,%17,%18,%19}, db, %21, 1, 1, %22;\n}"
               : R8("+f", 0), R8("+f", 8)
               : "r"(a[0]), "r"(a[1]), "r"(a[2]), "r"(a[3]), "r"(b), "n"(ACC), "n"(TB), "n"(dhi(SBO, 0)));
}

struct RowConst { float c[2][4], s[2][4]; };
__device__ __forceinline__ void rot(float& c, float& s, float dc, float ds) {
  const float n = c * dc - s * ds;
  s = s * dc + c * ds;
  c = n;
}
__device__ __forceinline__ void row_const(RowConst& r, int lane) {
  const int g = lane >> 2, t = lane & 3;
#pragma unroll
  for (int h = 0; h < 2; h++) {
    const float w = (float)(2 * g + h) * 0.02454369260617026f;
    float c, s, dc, ds;
    __sincosf(w * (float)(4 * t), &s, &c);
    __sincosf(w, &ds, &dc);
#pragma unroll
    for (int k = 0; k < 4; k++) {
      r.c[h][2 * (k & 1) + (k >> 1)] = c; r.s[h][2 * (k & 1) + (k >> 1)] = s;
      if (k < 3) rot(c, s, dc, ds);
    }
  }
}
template <int NR> __device__ __forceinline__ void row_step1(uint32_t sb, const uint32_t (*a)[8], float (*z)[16]) {
  const uint32_t d = dlo(sb + RMAT, 128);
#pragma unroll
  for (int r = 0; r < NR; r++) {
    wgmma32rs<0, 0, 512>(z[r], a[r], d);
    wgmma32rs<1, 0, 512>(z[r], a[r] + 4, d + (256 >> 4));
  }
  wg_commit();
}
template <int NR> __device__ __forceinline__ void row_twiddle(const RowConst& rc, uint32_t (*a)[8], float (*z)[16]) {
#pragma unroll
  for (int r = 0; r < NR; r++) {
    keep<16>(z[r]);
#pragma unroll
    for (int h = 0; h < 2; h++)
#pragma unroll
      for (int u = 0; u < 2; u++) {
        const float r0 = z[r][8 * u + 2 * h], r1 = z[r][8 * u + 2 * h + 1], i0 = z[r][8 * u + 4 + 2 * h], i1 = z[r][8 * u + 5 + 2 * h];
        const float c0 = rc.c[h][2 * u], s0 = rc.s[h][2 * u], c1 = rc.c[h][2 * u + 1], s1 = rc.s[h][2 * u + 1];
        a[r][4 * h + u] = movm(pack(i0 * c0 - r0 * s0, i1 * c1 - r1 * s1));
        a[r][4 * h + 2 + u] = movm(pack(r0 * c0 + i0 * s0, r1 * c1 + i1 * s1));
      }
    keepu<8>(a[r]);
  }
}
template <int NR> __device__ __forceinline__ void row_step2(uint32_t sb, const uint32_t (*a)[8], float (*z)[16]) {
  const uint32_t d = dlo(sb + RMAT, 512);
#pragma unroll
  for (int r = 0; r < NR; r++) {
    wgmma32rs<0, 1, 128>(z[r], a[r], d);
    wgmma32rs<1, 1, 128>(z[r], a[r] + 4, d + (1024 >> 4));
  }
  wg_commit();
}

struct Params {
  const __nv_bfloat16* x;
  unsigned char* scr;
  void* out;
  uint32_t zero;
  uint32_t tab[132];
  const __nv_bfloat16 *wr, *wi, *b1, *b2;
};

template <int NR>
__device__ __forceinline__ void row_ifft(const RowConst& rc, uint32_t sb, unsigned char* scr, int b, int lane, int q, int i0) {
  const int g = lane >> 2, t = lane & 3;
  const int col = t >> 1;
  uint32_t za[2], A[NR][8];
#pragma unroll
  for (int h = 0; h < 2; h++) {
    const int kl = 16 * (t & 1) + 2 * g + h, p = col ? 128 - kl : kl;
    za[h] = sb + S0 + p * 128 + (((4 * q + i0) ^ ((p >> 1) & 15)) << 3) + col * 4;
  }
  const int stp = col ? -4096 : 4096;
  float z[NR][16];
  mbar_wait(sb + MISC + 8 * B_Z);
#pragma unroll
  for (int r = 0; r < NR; r++)
#pragma unroll
    for (int j = 0; j < 8; j++)
      A[r][j] = lds32((j ? za[j & 1] + (j >> 1) * stp : lane == 2 ? za[0] - SLOT : za[0]) ^ (r << 3));
  wg_fence();
  row_step1<NR>(sb, A, z);
  wg_wait<0>();
  row_twiddle<NR>(rc, A, z);
  wg_fence();
  row_step2<NR>(sb, A, z);
  unsigned char* sp = scr + G_S + ((b >> 3) * 128 + 32 * i0 + 4 * (b & 7) + q) * 1024 + col * 512 + (t & 1) * 64 + g * 8;
  wg_wait<0>();
#pragma unroll
  for (int r = 0; r < NR; r++) {
    keep<16>(z[r]);
#pragma unroll
    for (int j = 0; j < 4; j++)
      stg64(sp + r * 32768 + j * 128, pack(z[r][4 * j], z[r][4 * j + 1]), pack(z[r][4 * j + 2], z[r][4 * j + 3]));
  }
  nb_arrive(NB_S, 288);
}

__device__ __forceinline__ void transpose_w(uint32_t sb, unsigned char* scr, int b, int ht) {
#pragma unroll 1
  for (int ch = 0; ch < 4; ch++) {
    unsigned char* wp = scr + G_WT + (ht >> 3) * 8192 + (b - 112) * 512 + ch * 128 +
                        (((ht & 7) * 16) ^ (((b & 1) * 2 + (ch >> 1)) << 5));
    uint32_t a = sb + ch * WCH + (4 * (ht & 7) * DF + (ht >> 3)) * 2;
    mbar_wait(sb + MISC + 8 * (B_WCH + ch));
#pragma unroll 1
    for (int n0 = 0; n0 < 18; n0 += 3) {
      uint32_t e[3][8];
#pragma unroll
      for (int n = 0; n < 3; n++)
#pragma unroll
        for (int i = 0; i < 8; i++)
          asm volatile("ld.shared.u16 %0, [%1];" : "=r"(e[n][i]) : "r"(a + n * 32 + (i >> 1) * DF * 2 + (i & 1) * 16448) : "memory");
#pragma unroll
      for (int n = 0; n < 3; n++)
        if (16 * (n0 + n) + (ht >> 3) < DF)
          asm volatile("st.global.v4.u32 [%0], {%1,%2,%3,%4};" ::"l"(wp + n * 16 * 8192),
                       "r"(__byte_perm(e[n][0], e[n][1], 0x5410)), "r"(__byte_perm(e[n][2], e[n][3], 0x5410)),
                       "r"(__byte_perm(e[n][4], e[n][5], 0x5410)), "r"(__byte_perm(e[n][6], e[n][7], 0x5410)) : "memory");
      a += 96;
      wp += 48 * 8192;
    }
  }
}

struct Ring {
  uint32_t s, ph;
  __device__ __forceinline__ void next() { if (++s == NS - 1) { s = 0; ph ^= 1; } }
};

struct Gemm {
  Ring r;
  uint32_t prev;
  uint32_t dA, dB, bars;
  uint32_t zr;
  bool lead;
  template <int TB, int KSTEP, int TAIL = 0>
  __device__ __forceinline__ void run(float* acc, int n, int accum) {
#pragma unroll 1
    for (int i = 0; i < n; i++) {
      mbar_wait(bars + 8 * r.s, r.ph);
      const uint32_t a = dA + r.s * (STAGE >> 4), w = dB + r.s * (STAGE >> 4);
      wg_fence();
#pragma unroll
      for (int k = 0; k < 4; k++) {
        wgmma128<TB>(acc, a + k * 128, w + k * KSTEP, k ? 1 : accum);
        if (k == TAIL) {
          wg_commit();
          wg_wait<1>();
          if (lead) mbar_arrive(prev);
          wg_fence();
        }
      }
      wg_commit();
      accum = 1;
      prev = bars + 8 * (B_EMPTY + r.s);
      r.next();
      if (!TB && TAIL && i == n - 2) r = {NS - 1, 0};
    }
  }
  __device__ __forceinline__ void drain() {
    wg_wait<0>();
    if (lead) mbar_arrive(prev);
    prev = bars + 8 * B_NONE;
  }
  template <int TB, int KSTEP, class F>
  __device__ __forceinline__ void tail(float* acc, int wg, F&& pre, uint32_t lda, uint32_t bias, uint32_t xdst, uint32_t xfull, int xfree) {
    constexpr int T = TM;
    uint32_t bb[8];
    auto prepare = [&]() {
      pre();
      mbar_wait(bars + 8 * xfree);
      if (TB) {
#pragma unroll
        for (int j = 0; j < 8; j++) bb[j] = lds32(bias + 16 * j);
      } else {
#pragma unroll
        for (int h = 0; h < 2; h++) asm volatile("ld.shared.u16 %0, [%1];" : "=r"(bb[h]) : "r"(bias + 16 * h) : "memory");
      }
    };
    auto send = [&](int j) {
      const float* a = acc + 32 + 16 * (j & 1) + (j & 2);
      st_async4(xdst + j * 4096, pack(a[0], a[1]), pack(a[4], a[5]), pack(a[8], a[9]), pack(a[12], a[13]), xfull + 4 * (j & 2));
    };
    if (TB && wg) {
      drain();
      renew<64>(acc);
      uint32_t A[T][16], w[T], em[T];
#pragma unroll
      for (int i = 0; i < T; i++) {
        mbar_wait(bars + 8 * r.s, r.ph);
#pragma unroll
        for (int k = 0; k < 4; k++) ldsm4t(lda + r.s * STAGE + k * 2048, A[i] + 4 * k);
        w[i] = dB + r.s * (STAGE >> 4);
        em[i] = bars + 8 * (B_EMPTY + r.s);
        r.next();
      }
      prepare();
      nb_sync(NB_T, 256);
      wg_fence();
#pragma unroll
      for (int n = 0; n < 4 * T; n++) wgmma64rs<1, TB, 1024, TB>(acc + 32, A[n >> 2] + 4 * (n & 3), w[n >> 2] + 512 + (n & 3) * KSTEP);
      wg_commit();
#pragma unroll
      for (int n = 0; n < 4 * T; n++) {
        wgmma64rs<1, TB, 1024, TB>(acc, A[n >> 2] + 4 * (n & 3), w[n >> 2] + (n & 3) * KSTEP);
        if (n == 3) { wg_commit(); wg_wait<1>(); keep<32>(acc + 32); send(0); wg_fence(); }
        if (n > 3 && n < 7) send(n - 3);
      }
      wg_commit();
      wg_wait<0>();
      keep<32>(acc);
      if (lead) {
#pragma unroll
        for (int i = 0; i < T; i++) mbar_arrive(em[i]);
      }
    } else {
      if (wg) { drain(); nb_sync(NB_T, 256); }
      run<TB, KSTEP, 1>(acc, T, 1);
      if (!wg) nb_arrive(NB_T, 256);
      prepare();
      drain();
      keep<64>(acc);
#pragma unroll
      for (int j = 0; j < 4; j++) send(j);
      if (TB) renew<32>(acc);
    }
    const float half = after_here(0.5f, zr);
#pragma unroll
    for (int j = 0; j < 32; j++)
      acc[j] = fmaf(acc[j], half, half * (TB ? ((j & 1) ? bhi(bb[j >> 2]) : blo(bb[j >> 2])) : blo(bb[(j >> 1) & 1])));
    pin<32>(acc, zr);
  }
};

template <bool BY_SM>
__global__ void __cluster_dims__(2, 1, 1) __launch_bounds__(NTHR, 1)
fused_kernel(const __grid_constant__ Params P, const __grid_constant__ CUtensorMap mW1, const __grid_constant__ CUtensorMap mW2,
             const __grid_constant__ CUtensorMap mX1) {
  extern __shared__ __align__(1024) unsigned char smem[];
#define GET_B uint32_t sm_, rk_;                                                                         \
  if (BY_SM) asm volatile("mov.u32 %0, %%smid;" : "=r"(sm_));                                            \
  else asm volatile("mov.u32 %0, %%ctaid.x;" : "=r"(sm_));                                                       \
  asm volatile("mov.u32 %0, %%cluster_ctarank;" : "=r"(rk_));                                            \
  const uint32_t tb_ = P.tab[(sm_ & ~1u) | rk_];                                                         \
  const int b = tb_ & 255, pb = ((tb_ >> 14) & 0x78) | ((tb_ >> 12) & 7);
#define cnt(c) (scr + G_CNT + 128 * (c))
#define ROLE_CTX                                                                                         \
  const uint32_t sb = __shfl_sync(0xffffffffu, (uint32_t)__cvta_generic_to_shared(smem), 0);             \
  int tid;                                                                                               \
  GET_B                                                                                                  \
  asm volatile("mov.u32 %0, %%tid.x;" : "=r"(tid));                                                      \
  const int lane = tid & 31, warp = __shfl_sync(0xffffffffu, tid >> 5, 0);                               \
  const bool main_cta = b < 128, g1_cta = b < 112;                                                       \
  const int rank = b & 1, dt = (b >> 1) & 3, wt = b >> 3;                                  \
  unsigned char* const scr = P.scr;                                                                      \
  auto bar = [&](int i) { return sb + MISC + 8 * i; };                                                   \
  (void)rank; (void)dt; (void)wt; (void)lane; (void)warp; (void)g1_cta; (void)pb;
  uint32_t L[2][8];
  {
    const uint32_t tx = threadIdx.x;
    const unsigned char* xp = (const unsigned char*)P.x + ((tx & 32) * 2048 + (tx >> 6) * 1024 + (tx & 2) * 256 + (tx & 1) * 64 + (tx & 28) * 2);
    GET_B
    (void)b; (void)pb;
    xp += tb_ & 0x1ff000;
    const uint32_t on = tx < 256;
#pragma unroll
    for (int i = 0; i < 8; i++)
      asm volatile("{\n.reg .pred p;\nsetp.ne.u32 p, %3, 0;\n@p ld.global.nc.L1::no_allocate.v2.u32 {%0,%1}, [%2];\n}"
                   : "=r"(L[i >> 2][2 * (i & 3)]), "=r"(L[i >> 2][2 * (i & 3) + 1]) : "l"(xp + (i >> 2) * 32768 + (i & 3) * 128), "r"(on));
  }
  if (threadIdx.x < 256) {
    asm volatile("barrier.cluster.arrive.relaxed.aligned;" ::: "memory");
    asm volatile("setmaxnreg.inc.sync.aligned.u32 208;");
    ROLE_CTX
    if (b > 128) return;
    const int g = lane >> 2, t = lane & 3, wg = warp >> 2;
    const uint32_t zr = P.zero & tid;
    const int hprio = (pb >> 3) & 7;
    RowConst rc;
    uint32_t hq[2][8];
    unsigned char* hp;
    auto store_h = [&]() {
#pragma unroll
      for (int r = 0; r < 2; r++)
#pragma unroll
        for (int j = 0; j < 4; j++) stg64(hp + r * 4096 + (j >> 1) * 32 * SLOT + (j & 1) * 8192, hq[r][2 * j], hq[r][2 * j + 1]);
      nb_arrive(NB_H, 288);
    };
    if (main_cta) {
      const int row0 = 128 * (pb >> 3) + 64 * (warp & 1) + 4 * (pb & 7) + (warp >> 1);
      const int col = t >> 1;
      row_const(rc, lane);
      hp = scr + G_H + ((2 * col * 32 + (row0 >> 6)) * 2) * 8192 + (row0 & 63) * 128 +
                          (((4 * (t & 1) + (g >> 1)) ^ (row0 & 7)) << 4) + (g & 1) * 8;
      uint32_t sta[4];
      {
        const uint32_t un = (warp >> 1) * 2 + col, sub = 8 * (warp & 1);
#pragma unroll
        for (int h = 0; h < 2; h++) {
          const int kl = 16 * (t & 1) + 2 * g + h, p = col ? 128 - kl : kl, r7 = (p >> 1) & 7;
          sta[h] = sb + S0 + ((p & 0xf0) + 8 * h + r7) * 128 + ((un ^ r7) << 4) + sub;
        }
        sta[2] = (lane & 29) ? sta[0] : col ? sta[0] - SLOT : sb + XTRA + (un << 4) + sub;
        sta[3] = (uint32_t)(uintptr_t)hp;
      }
      pin<16>(&rc, zr); pin<4>(sta, zr);
      float v[2][16], s1[2], s2[2];
#pragma unroll
      for (int r = 0; r < 2; r++) {
        const float piv = blo(__shfl_sync(0xffffffffu, L[r][0], 0));
        s1[r] = 0.f; s2[r] = 0.f;
#pragma unroll
        for (int j = 0; j < 8; j++) { v[r][2 * j] = blo(L[r][j]) - piv; v[r][2 * j + 1] = bhi(L[r][j]) - piv; }
#pragma unroll
        for (int i = 0; i < 16; i++) { s1[r] += v[r][i]; s2[r] = fmaf(v[r][i], v[r][i], s2[r]); }
      }
#pragma unroll
      for (int o = 16; o > 0; o >>= 1)
#pragma unroll
        for (int r = 0; r < 2; r++) {
          s1[r] += __shfl_xor_sync(0xffffffffu, s1[r], o);
          s2[r] += __shfl_xor_sync(0xffffffffu, s2[r], o);
        }
#pragma unroll
      for (int r = 0; r < 2; r++) {
        s1[r] *= -1.f / DM;
        s2[r] = fmaxf(fmaf(-s1[r], s1[r], s2[r] * (1.f / DM)), 0.f);
        const float a2 = rsqrt_fast(fmaf(s2[r], 1.f + 1e-5f, 1e-10f)), c2 = s1[r] * a2;
#pragma unroll
        for (int j = 0; j < 8; j++) hq[r][j] = pack(fmaf(v[r][2 * j], a2, c2), fmaf(v[r][2 * j + 1], a2, c2));
      }
      if (hprio < H_LATE) store_h();
      nb_sync(NB_R, 384);
      const float eps = after_here(1e-5f, zr);
#pragma unroll
      for (int r = 0; r < 2; r++) {
        const float a1 = rsqrt_fast(s2[r] + eps), c1 = s1[r] * a1;
#pragma unroll
        for (int j = 0; j < 8; j++) L[r][j] = pack(fmaf(v[r][2 * j], a1, c1), fmaf(v[r][2 * j + 1], a1, c1));
      }
      wg_fence();
      row_step1<2>(sb, L, v);
      wg_wait<0>();
      row_twiddle<2>(rc, L, v);
      wg_fence();
      row_step2<2>(sb, L, v);
      if (hprio >= H_LATE) store_h();
      wg_wait<0>();
      keep<16>(v[0]);
      keep<16>(v[1]);
      const uint32_t cj = col << 31;
      const int stp = col ? -4096 : 4096;
#pragma unroll
      for (int j = 0; j < 4; j++)
#pragma unroll
        for (int h = 0; h < 2; h++) {
          const uint32_t a = (j | h) ? sta[h] + j * stp : sta[2];
          const uint32_t z0 = pack(v[0][4 * j + 2 * h + 1], v[0][4 * j + 2 * h]) ^ cj;
          const uint32_t z1 = pack(v[1][4 * j + 2 * h + 1], v[1][4 * j + 2 * h]) ^ cj;
          if (!(j | h) && !(lane & 29))
            asm volatile("st.shared.v2.u32 [%0], {%1,%2};" ::"r"(a ^ 16), "r"(z0 ^ 0x80000000u), "r"(z1 ^ 0x80000000u) : "memory");
          asm volatile("st.shared.v2.u32 [%0], {%1,%2};" ::"r"(a), "r"(z0), "r"(z1) : "memory");
        }
      fence_async_smem();
      __syncwarp();
      if (lane == 0) mbar_arrive(bar(B_STG));
    } else {
      nb_sync(NB_R, 384);
    }
    const int pcol = b == 0 ? 128 : (b & 0x70) | ((b & 7) << 1) | ((b >> 3) & 1);
    const int k1c = 8 * warp + g;
    uint32_t fa[8][4];
    {
      float c, s, dc, ds;
      __sincosf((float)(k1c * t) * 0.09817477042468103f, &s, &c);
      __sincosf((float)(k1c & 15) * 0.39269908169872414f, &ds, &dc);
#pragma unroll
      for (int n = 0; n < 8; n++) {
        fa[n >> 1][2 * (n & 1)] = pack(c, s);
        fa[n >> 1][2 * (n & 1) + 1] = pack(-s, c);
        if (n < 7) rot(c, s, dc, ds);
      }
#pragma unroll
      for (int n = 0; n < 16; n++) fa[4 + (n >> 2)][n & 3] = fa[n >> 2][n & 3] ^ ((g & 1) ? 0x80008000u : 0u);
      keepu<16>(fa[4]);
      pin<16>(fa[4], zr);
    }
    const uint32_t peer = mapa(sb, rank ^ 1);
    float c[32];
    const uint32_t dB1 = dlo(sb + S1, 1024);
    const uint32_t lda = sb + 8192 + ((lane & 7) + 8 * (lane >> 4)) * 128 + (((2 * (warp & 3) + ((lane >> 3) & 1)) ^ (lane & 7)) << 4);
    Gemm gm;
    gm.r = {0, 0}; gm.bars = bar(0); gm.prev = bar(B_NONE); gm.lead = (tid & 127) == 0; gm.zr = zr;
    if (g1_cta) {
      float acc[64];
      gm.dA = dlo(sb + wg * 8192, 8192); gm.dB = dlo(sb + SLOT, 8192);
      gm.run<1, 128>(acc, 16 - TM, 0);
      gm.tail<1, 128>(acc, wg, []() {}, lda, sb + BIAS + 4 * t, peer + S0 + tid * 16, peer + MISC + 8 * B_XFULL1 + 16 * wg, B_XFREE1);
      if (wg) mbar_wait(bar(B_CF));
      unsigned char* up = scr + G_U + (dt * 28 + 2 * wt + rank) * SLOT + warp * 2048 + lane * 4;
#pragma unroll
      for (int h = 0; h < 2; h++) {
        mbar_wait(bar(B_XFULL1 + h) + 16 * wg);
        const uint4 oa = lds128(sb + S0 + tid * 16 + h * 8192), ob = lds128(sb + S0 + tid * 16 + h * 8192 + 4096);
        const uint32_t o[8] = {oa.x, oa.y, oa.z, oa.w, ob.x, ob.y, ob.z, ob.w};
        float y[16], th[16];
#pragma unroll
        for (int i = 0; i < 16; i++) {
          y[i] = fmaf((i & 1) ? bhi(o[i >> 1]) : blo(o[i >> 1]), 0.5f, acc[4 * (i >> 1) + 2 * h + (i & 1)]);
          th[i] = tanh_fast(y[i] * fmaf(y[i] * y[i], 0.285419265090401f, 1.5957691216057308f));
        }
#pragma unroll
        for (int nt = 0; nt < 8; nt++)
          stg32(up + nt * 128 + h * 1024, pack(fmaf(y[2 * nt], th[2 * nt], y[2 * nt]), fmaf(y[2 * nt + 1], th[2 * nt + 1], y[2 * nt + 1])));
      }
      nb_arrive(NB_U, 288);
    } else if (main_cta) {
      mbar_wait(bar(B_XFREE1));
    }
    if (!(g1_cta && wg)) mbar_wait(bar(B_CF));
    wg_fence();
    wgmma64rs<0, 0, 128>(c, fa[0], dB1);
#pragma unroll
    for (int i = 1; i < 8; i++) wgmma64rs<1, 0, 128>(c, fa[i], dB1 + i * (2048 >> 4));
    wg_commit();
    float twc[8], tws[8], rho;
    uint32_t wo[4];
    {
      float w = after_here(0.0030679615757712823f, zr);
      float c, s, dc, ds;
      __sincosf(fmaf((float)pcol, 2.f * w, 0.7853981633974483f), &ds, &dc);
      rho = __fdividef(dc, ds);
      w *= (float)k1c;
      __sincosf(w * (float)t, &s, &c);
      c *= ds * 0.0013810679320049757f; s *= ds * 0.0013810679320049757f;
      __sincosf(w * 4.f, &ds, &dc);
#pragma unroll
      for (int n = 0; n < 8; n++) {
        twc[n] = c; tws[n] = s;
        if (n < 7) rot(c, s, dc, ds);
      }
      const int j0 = k1c + 64 * t, jn = SEQ - j0;
      wo[0] = sb + S3 + (j0 ^ (t << 3)) * 4;
      wo[1] = sb + S3 + 8192 + (jn ^ ((jn >> 3) & 24)) * 4;
      wo[2] = j0 ? wo[1] : wo[1] - 8192;
      wo[3] = __float_as_uint(rho) ^ __float_as_uint(c) ^ __float_as_uint(s);
      pin<4>(wo, zr);
    }
    wg_wait<0>();
    keep<32>(c);
    if ((tid & 127) == 0) mbar_arrive(bar(B_S1));
    uint32_t ap[16];
    float d[32];
    const uint32_t dG = dlo(sb + S2, 128);
#pragma unroll
    for (int nt = 0; nt < 8; nt++) {
      ap[2 * nt] = pack(c[4 * nt] * twc[nt] + c[4 * nt + 2] * tws[nt], c[4 * nt + 2] * twc[nt] - c[4 * nt] * tws[nt]);
      ap[2 * nt + 1] = pack(c[4 * nt + 1] * twc[nt] + c[4 * nt + 3] * tws[nt], c[4 * nt + 3] * twc[nt] - c[4 * nt + 1] * tws[nt]);
      if (nt & 1) {
        wg_fence();
        if (nt == 1) wgmma64rs<0, 0, 1024>(d, ap, dG); else wgmma64rs<1, 0, 1024>(d, ap + 2 * nt - 2, dG + (nt >> 1) * (256 >> 4));
      }
    }
    wg_commit();
    uint32_t wq[16];
    mbar_wait(bar(B_WQ));
#pragma unroll
    for (int i = 0; i < 8; i++) { wq[2 * i] = lds32(wo[0] + i * 1024); wq[2 * i + 1] = lds32(wo[i ? 1 : 2] - i * 1024); }
    wg_wait<0>();
    keep<32>(d);
#pragma unroll
    for (int nt = 0; nt < 8; nt++) {
      const float ar = d[4 * nt], ai = d[4 * nt + 1], br = d[4 * nt + 2], bi = d[4 * nt + 3];
      const float w1r = blo(wq[2 * nt]), w1i = bhi(wq[2 * nt]), w2r = blo(wq[2 * nt + 1]), w2i = bhi(wq[2 * nt + 1]);
      const float pr = fmaf(rho, ar, -bi), pi = fmaf(rho, ai, br), qr = fmaf(rho, br, -ai), qi = fmaf(rho, bi, ar);
      const float xr = pr * w1r - pi * w1i, xi = pr * w1i + pi * w1r, yr = qr * w2r + qi * w2i, yi = qi * w2r - qr * w2i;
      ap[2 * nt] = pack(fmaf(rho, xi, -yr), fmaf(rho, xr, yi));
      ap[2 * nt + 1] = pack(fmaf(rho, yi, -xr), fmaf(rho, yr, xi));
      if (nt & 1) {
        wg_fence();
        if (nt == 1) wgmma64rs<0, 0, 1024>(c, ap, dG); else wgmma64rs<1, 0, 1024>(c, ap + 2 * nt - 2, dG + (nt >> 1) * (256 >> 4));
      }
    }
    wg_commit();
#pragma unroll
    for (int i = 0; i < 8; i++) {
      const uint32_t cc = __byte_perm(fa[i][0], fa[i][2], 0x5410), ss = __byte_perm(fa[i][0], fa[i][2], 0x7632);
      fa[i][3] = __byte_perm(fa[i][1], fa[i][3], 0x7632);
      fa[i][0] = cc; fa[i][1] = ss ^ 0x80008000u; fa[i][2] = ss;
      keepu<4>(fa[i]);
    }
    mbar_wait(bar(B_S1));
    wg_wait<0>();
    keep<32>(c);
#pragma unroll
    for (int nt = 0; nt < 8; nt++) {
      ap[2 * nt] = pack(c[4 * nt] * twc[nt] + c[4 * nt + 1] * tws[nt], c[4 * nt + 2] * twc[nt] + c[4 * nt + 3] * tws[nt]);
      ap[2 * nt + 1] = pack(c[4 * nt + 1] * twc[nt] - c[4 * nt] * tws[nt], c[4 * nt + 3] * twc[nt] - c[4 * nt + 2] * tws[nt]);
    }
    {
      const int r = lane & 7, mi = lane >> 3;
      const uint32_t a = sb + S1 + warp * 2048 + (mi & 1) * 1024 + (mi >> 1) * 128 + (2 * (r & 3) + (r >> 2)) * 16;
#pragma unroll
      for (int i = 0; i < 4; i++) stsm4(a + i * 256, ap[4 * i], ap[4 * i + 1], ap[4 * i + 2], ap[4 * i + 3]);
    }
    fence_async_smem();
    nb_sync(NB_C, 256);
    wg_fence();
    wgmma64rs<0, 1, 128>(c, fa[0], dB1);
#pragma unroll
    for (int i = 1; i < 8; i++) wgmma64rs<1, 1, 128>(c, fa[i], dB1 + i * (2048 >> 4));
    wg_commit();
    unsigned char* zq = scr + G_Z + (k1c >> 2) * 8 * SLOT + (pcol & 127) * 128 + (((4 * t + (g & 3)) ^ ((pcol >> 1) & 15)) << 3);
    wg_wait<0>();
    keep<32>(c);
    if ((tid & 127) == 0) mbar_arrive(bar(B_S4));
    const bool zlate = g1_cta && (pcol & 127);
    if (!zlate) {
      if (pcol & 127) {
#pragma unroll
        for (int nt = 0; nt < 8; nt++) stg64(zq + nt * SLOT, pack(c[4 * nt], c[4 * nt + 2]), pack(-c[4 * nt + 1], c[4 * nt + 3]));
      } else {
#pragma unroll
        for (int nt = 0; nt < 8; nt++)
          stg32(zq + nt * SLOT + (pcol >> 5), pcol ? pack(-c[4 * nt + 1], c[4 * nt + 3]) : pack(c[4 * nt], c[4 * nt + 2]));
      }
      nb_arrive(NB_Z, 288);
    }
    if (main_cta) {
      float acc[64];
      gm.dA = dlo(sb + SLOT + wg * 8192, 8192); gm.dB = dlo(sb, 128);
      const int nz = ZK + (wg ? ZST : 0);
      gm.run<0, 16>(acc, 1, 0);
#pragma unroll
      for (int nt = 0; nt < 8; nt++)
        asm volatile("{\n.reg .pred p;\nsetp.ne.u32 p, %3, 0;\n@p st.global.v2.u32 [%0], {%1,%2};\n}" ::"l"(zq + nt * SLOT),
                     "r"(pack(c[4 * nt], c[4 * nt + 2])), "r"(pack(-c[4 * nt + 1], c[4 * nt + 3])), "r"((uint32_t)zlate) : "memory");
      if (zlate) nb_arrive(NB_Z, 288);
      gm.run<0, 16>(acc, nz - 1, 1);
      gm.drain();
      row_ifft<2>(rc, sb, scr, b, lane, warp >> 1, 2 * (warp & 1));
      gm.run<0, 16>(acc, 14 - TM - nz, 1);
      const int fo = (wt * 128 + warp * 16 + (lane >> 3)) * 1024 + (dt * 2 + rank) * 128 + (lane & 7) * 16;
      uint4 xv[4];
      auto load_x = [&]() {
#pragma unroll
      for (int i = 0; i < 4; i++)
        asm volatile("ld.global.nc.L1::no_allocate.v4.u32 {%0,%1,%2,%3}, [%4];" : "=r"(xv[i].x), "=r"(xv[i].y), "=r"(xv[i].z), "=r"(xv[i].w)
                     : "l"((const unsigned char*)P.x + fo + i * 4096) : "memory");
      };
      gm.tail<0, 16>(acc, wg, load_x, 0, sb + BIAS + 128 + (warp * 16 + g) * 2, peer + S1 + tid * 16, peer + MISC + 8 * B_XFULL2 + 16 * wg,
                     B_XFREE2);
      const uint32_t ga = sb + S1 + warp * 512;
      uint4 gv[4], sv[4];
      auto load_s = [&]() {
#pragma unroll
        for (int i = 0; i < 4; i++)
          asm volatile("ld.relaxed.gpu.global.v4.u32 {%0,%1,%2,%3}, [%4];" : "=r"(sv[i].x), "=r"(sv[i].y), "=r"(sv[i].z), "=r"(sv[i].w)
                       : "l"(scr + G_S + fo + i * 4096) : "memory");
      };
      bool have_s = false;
#pragma unroll
      for (int h = 0; h < 2; h++) {
        mbar_wait(bar(B_XFULL2 + h) + 16 * wg);
        if (!have_s && mbar_test(bar(B_FIN))) { load_s(); have_s = true; }
        const uint4 oa = lds128(sb + S1 + tid * 16 + h * 8192), ob = lds128(sb + S1 + tid * 16 + h * 8192 + 4096);
        const uint32_t o[8] = {oa.x, oa.y, oa.z, oa.w, ob.x, ob.y, ob.z, ob.w};
        uint32_t gs[8];
#pragma unroll
        for (int nt = 0; nt < 8; nt++) {
          const float y0 = fmaf(blo(o[nt]), 0.5f, acc[4 * nt + 2 * h]), y1 = fmaf(bhi(o[nt]), 0.5f, acc[4 * nt + 2 * h + 1]);
          gs[nt] = pack(fmaf(y0, tanh_fast(y0), y0), fmaf(y1, tanh_fast(y1), y1));
        }
        const uint32_t a = ga + h * 8192 + (lane & 4) * 1024 + (lane & 3) * 128 + (((lane >> 3) ^ (lane & 7)) << 4);
        __syncwarp();
        stsm4(a, gs[0], gs[1], gs[2], gs[3]);
        stsm4(a ^ 64, gs[4], gs[5], gs[6], gs[7]);
      }
      __syncwarp();
#pragma unroll
      for (int i = 0; i < 4; i++) gv[i] = lds128(ga + i * 4096 + (lane >> 3) * 128 + (((lane & 7) ^ (4 * (i & 1) + (lane >> 3))) << 4));
      if (!have_s) { mbar_wait(bar(B_FIN)); load_s(); }
#pragma unroll
      for (int i = 0; i < 4; i++)
        asm volatile("st.global.v4.u32 [%0], {%1,%2,%3,%4};" ::"l"((unsigned char*)P.out + fo + i * 4096), "r"(hfma2(sv[i].x, gv[i].x, xv[i].x)),
                     "r"(hfma2(sv[i].y, gv[i].y, xv[i].y)), "r"(hfma2(sv[i].z, gv[i].z, xv[i].z)), "r"(hfma2(sv[i].w, gv[i].w, xv[i].w)) : "memory");
    }
  } else if (threadIdx.x < 384) {
    asm volatile("setmaxnreg.dec.sync.aligned.u32 56;");
    ROLE_CTX
    if (b > 128) return;
    asm volatile("barrier.cluster.arrive.relaxed.aligned;" ::: "memory");
    const int hw = warp - 8, ht = tid - 256, kg = ht & 3;
    {
      const int pos = (ht >> 2) & 7, k1 = 2 * pos + (hw >> 1);
      float c, s, dc, ds;
      __sincosf((float)((k1 * 2 * kg + 4 * (hw & 1)) & 15) * 0.39269908169872414f, &s, &c);
      __sincosf((float)k1 * 0.39269908169872414f, &ds, &dc);
      const uint32_t e0 = pack(c, s), sg = (hw >> 1) ? 0x80008000u : 0u;
      rot(c, s, dc, ds);
      const uint32_t e1 = pack(c, s);
      asm volatile("st.shared.v4.u32 [%0], {%1,%2,%3,%4};" ::"r"(sb + RMAT + hw * 512 + kg * 128 + pos * 16), "r"(e0), "r"(e1),
                   "r"(e0 ^ sg), "r"(e1 ^ sg) : "memory");
      fence_async_smem();
    }
    asm volatile("barrier.cluster.wait.aligned;" ::: "memory");
    nb_arrive(NB_R, 384);
    if (main_cta && !g1_cta) {
      transpose_w(sb, scr, b, ht);
      nb_sync(NB_HLP, 128);
      if (hw == 3 && elect_one()) { signal(cnt(C_W), 1); mbar_arrive(bar(B_WDONE)); }
      __syncwarp();
    }
    if (g1_cta) mbar_wait(bar(B_STG));
    {
      const int k2 = ht >> 2;
      float c, s, dc, ds;
      __sincosf((float)((k2 * 8 * kg) & 31) * 0.19634954084936207f, &s, &c);
      __sincosf((float)k2 * 0.19634954084936207f, &ds, &dc);
#pragma unroll
      for (int q = 0; q < 2; q++) {
        uint32_t re[4], im[4];
#pragma unroll
        for (int i = 0; i < 4; i++) {
          re[i] = pack(c, s); im[i] = pack(-s, c);
          rot(c, s, dc, ds);
        }
        const uint32_t a = sb + S2 + ((k2 >> 2) * 8 + kg * 2 + q) * 128 + (k2 & 3) * 32;
        asm volatile("st.shared.v4.u32 [%0], {%1,%2,%3,%4};" ::"r"(a), "r"(re[0]), "r"(re[1]), "r"(re[2]), "r"(re[3]) : "memory");
        asm volatile("st.shared.v4.u32 [%0], {%1,%2,%3,%4};" ::"r"(a + 16), "r"(im[0]), "r"(im[1]), "r"(im[2]), "r"(im[3]) : "memory");
      }
      if (!main_cta) {
        mbar_wait(bar(B_WQ));
#pragma unroll 1
        for (int i = ht; i < 2 * 1025; i += 128) {
          const int j = i >> 1, jn = (SEQ - j) & (SEQ - 1);
          const uint32_t a0 = sb + S3 + (i & 1) * 8192, a = a0 + (j ^ ((j >> 3) & 24)) * 4, an = a0 + (jn ^ ((jn >> 3) & 24)) * 4;
          const uint32_t u = lds32(a), v = lds32(an), w = pack(0.5f * (blo(u) + blo(v)), 0.5f * (bhi(u) - bhi(v)));
          asm volatile("st.shared.u32 [%0], %1;" ::"r"(an), "r"(w ^ 0x80000000u) : "memory");
          asm volatile("st.shared.u32 [%0], %1;" ::"r"(a), "r"(w) : "memory");
        }
      }
      fence_async_smem();
      __syncwarp();
      if (lane == 0) mbar_arrive(bar(B_CF));
    }
  } else {
    asm volatile("setmaxnreg.dec.sync.aligned.u32 40;");
    ROLE_CTX
    if (b > 128) {
      const uint32_t t0 = clk();
      while (warp == 12 && clk() - t0 < 5000) __nanosleep(500);
      return;
    }
    if (warp == 12) {
      if (elect_one()) {
#pragma unroll
        for (int i = 0; i <= B_NONE; i++) mbar_init(bar(i), i < NS ? 1 : i < 2 * NS ? 2 : 0x7ffff);
        if (!g1_cta) {
#pragma unroll
          for (int i = B_WCH; i < B_STG; i++) mbar_init(bar(i), 1);
        }
        asm volatile("fence.mbarrier_init.release.cluster;" ::: "memory");
      }
      __syncwarp();
      asm volatile("barrier.cluster.arrive.relaxed.aligned;" ::: "memory");
      if (main_cta && elect_one()) {
        Ring r = {0, 1};
        if (g1_cta) {
          const int c0 = wt * 128 + rank * 64;
#pragma unroll 1
          for (int k = rank * 1024; k < rank * 1024 + 1024; k += 64) {
            const uint32_t d = sb + SLOT + r.s * STAGE, f = bar(B_FULL) + 8 * r.s;
            mbar_wait(f + 8 * NS, r.ph);
            tma2d(d, &mW1, c0, k, f);
            tma2d(d + 8192, &mW1, c0 ^ 64, k, f);
            r.next();
          }
        } else {
#pragma unroll 1
          for (int i = 0; i < 4; i++) {
            if (i >= 2) mbar_wait(bar(B_WCH + i - 2));
            const int go = ((b - 112) * 4 + i) * 16448;
            bulk_load(sb + i * WCH, (const unsigned char*)P.wr + go, 16448, bar(B_WCH + i));
            bulk_load(sb + i * WCH + 16448, (const unsigned char*)P.wi + go, 16448, bar(B_WCH + i));
            mbar_expect(bar(B_WCH + i), 32896);
          }
          mbar_wait(bar(B_WDONE));
        }
        if (g1_cta) mbar_wait(bar(B_FULL), 1);
#pragma unroll 1
        for (int k = rank * 896; k < rank * 896 + 896; k += 64) {
          const uint32_t d = sb + SLOT + r.s * STAGE, f = bar(B_FULL) + 8 * r.s;
          mbar_wait(f + 8 * NS, r.ph);
          tma2d(d, &mW2, wt * 128, k, f);
          tma2d(d + 8192, &mW2, wt * 128 + 64, k, f);
          r.next();
          if (k == rank * 896 + 768) r = {NS - 1, 0};
          if (k == rank * 896 + 64 * (GZ - 1)) mbar_wait(bar(B_Z));
        }
      }
    } else if (warp == 15) {
      if (elect_one()) {
#pragma unroll
        for (int i = B_STG; i < B_COUNT; i++) mbar_init(bar(i), i == B_STG ? 8 : i == B_CF ? 5 : i <= B_S1 ? 2 : 1);
        asm volatile("fence.mbarrier_init.release.cluster;" ::: "memory");
      }
      __syncwarp();
      asm volatile("barrier.cluster.arrive.relaxed.aligned;" ::: "memory");
      const void *ch = cnt(C_H + (pb >> 6)), *cu = cnt(C_U + dt * 2 + (wt >= 7)), *cz = cnt(C_Z), *cs = cnt(C_S + (wt & 15));
      const unsigned ih = 1u << (4 * ((pb >> 3) & 7)), iu = 1u << (2 * (wt >= 7 ? wt - 7 : wt) + rank);
      asm volatile("" : "+l"(ch), "+l"(cu), "+l"(cz), "+l"(cs));
      if (main_cta) {
        nb_sync(NB_H, 288);
        if (elect_one()) signal(ch, ih);
        __syncwarp();
      }
      if (g1_cta) {
        nb_sync(NB_U, 288);
        if (elect_one()) signal(cu, iu);
        __syncwarp();
      }
      nb_sync(NB_Z, 288);
      if (elect_one()) signal(cz, main_cta ? 1 : 128);
      __syncwarp();
      if (main_cta) {
        nb_sync(NB_S, 288);
        if (elect_one()) signal(cs, 1);
      }
    } else {
      asm volatile("barrier.cluster.arrive.relaxed.aligned;" ::: "memory");
      const unsigned ep = ld_relaxed(cnt(C_EPOCH));
      asm volatile("barrier.cluster.wait.aligned;" ::: "memory");
      if (warp == 13) {
        if (main_cta && elect_one()) {
          Ring r = {0, 1};
          unsigned seen = 0;
          if (g1_cta) {
            const unsigned char* src = scr + G_H + (dt * 32 + rank * 16) * SLOT;
#pragma unroll 1
            for (int i = 0; i < 16; i++) {
              const uint32_t d = sb + r.s * STAGE, f = bar(B_FULL) + 8 * r.s;
              mbar_wait(f + 8 * NS, r.ph);
              poll(cnt(C_H + rank), ep * 0x88888888u, 8u << (2 * (i & 14)), seen);
              bulk_load(d, src, SLOT, f);
              mbar_expect(f, STAGE);
              src += SLOT;
              r.next();
            }
          } else {
            mbar_wait(bar(B_WDONE));
          }
          seen = 0;
          const unsigned char* src = scr + G_U + (dt * 28 + rank * 14) * SLOT + rank * 8192;
          const int oth = rank ? -8192 : 8192;
#pragma unroll 1
          for (int i = 0; i < 14; i++) {
            const uint32_t d = sb + r.s * STAGE, f = bar(B_FULL) + 8 * r.s;
            mbar_wait(f + 8 * NS, r.ph);
            poll(cnt(C_U + dt * 2 + rank), ep * 0x3fffu, 1u << i, seen);
            bulk_load(d, src, 8192, f);
            bulk_load(d + 8192, src + oth, 8192, f);
            mbar_expect(f, STAGE);
            src += SLOT;
            r.next();
            if (i == 12) r = {NS - 1, 0};
            if (i == GZ - 1) mbar_wait(bar(B_Z));
          }
        }
      } else if (elect_one()) {
        const uint32_t peer = mapa(sb, rank ^ 1);
#pragma unroll
        for (int i = 0; i < 8; i++) mbar_expect(bar(B_XFULL1 + i), SLOT / 4);
        if (main_cta) {
          bulk_load(sb + BIAS, P.b1 + (g1_cta ? wt : 0) * 128 + rank * 64, 128, bar(B_XFREE1));
          bulk_load(sb + BIAS + 128, P.b2 + wt * 128, 256, bar(B_XFREE1));
          mbar_expect(bar(B_XFREE1), 388);
          prefetch_map(&mX1);
          mbar_wait(bar(B_STG));
          if (g1_cta) mbar_wait(bar(B_FULL + 3));
          bulk_store(scr + G_X1 + 128 * SLOT + pb * 128, sb + XTRA, 128);
          const uint32_t t1 = clk();
#pragma unroll 1
          for (int n = 0; n < 4; n++) {
            wait_until(t1, n * X1_DT);
            tma2d_store(&mX1, pb * 64, 32 * n, sb + S0 + n * 4096);
          }
          bulk_commit();
          bulk_wait_all();
          asm volatile("st.async.weak.shared::cluster.mbarrier::complete_tx::bytes.b32 [%0], %1, [%2];" ::"r"(peer + WHO), "r"(b),
                       "r"(peer + MISC + 8 * B_XFREE1) : "memory");
          mbar_arrive_cluster(peer + MISC + 8 * B_XFREE1);
          signal(cnt(C_X), 1);
          prefetch_map(&mW2);
        }
        poll(cnt(C_X), ep * 128, 128);
        bulk_load(sb + S1, scr + G_X1 + b * SLOT, SLOT, bar(B_CF));
        mbar_expect(bar(B_CF), SLOT);
        const int pcol = b == 0 ? 128 : (b & 0x70) | ((b & 7) << 1) | ((b >> 3) & 1);
        const uint32_t wb = bar(B_WQ);
        poll(cnt(C_W), ep * 16, 16);
        if (g1_cta) mbar_wait(bar(B_XFULL1));
        bulk_load(sb + S3, scr + G_WT + pcol * 8192, 8192, wb);
        bulk_load(sb + S3 + 8192, scr + G_WT + (256 - pcol) * 8192, 8192, wb);
        mbar_expect(wb, SLOT);
        if (main_cta) {
          mbar_wait(bar(B_XFREE1));
          asm volatile("{\n.reg .pred p;\nsetp.ne.u32 p, %0, %1;\n@p trap;\n}" ::"r"(lds32(sb + WHO)), "r"(b ^ 1));
          mbar_wait(bar(B_S4));
          mbar_arrive_cluster(peer + MISC + 8 * B_XFREE2);
          poll(cnt(C_Z), ep * 256, 256);
          bulk_load(sb + S0, scr + G_Z + b * SLOT, SLOT, bar(B_Z));
          mbar_expect(bar(B_Z), SLOT);
          if (b == 0) asm volatile("st.relaxed.gpu.global.u32 [%0], %1;" ::"l"(cnt(C_EPOCH)), "r"(ep + 1) : "memory");
          poll(cnt(C_S + wt), ep * 8, 8);
          mbar_arrive(bar(B_FIN));
        }
      }
    }
  }
}

typedef CUresult (*EncodeFn)(CUtensorMap*, CUtensorMapDataType, cuuint32_t, void*, const cuuint64_t*, const cuuint64_t*,
                             const cuuint32_t*, const cuuint32_t*, CUtensorMapInterleave, CUtensorMapSwizzle,
                             CUtensorMapL2promotion, CUtensorMapFloatOOBfill);

CUtensorMap make_map(EncodeFn enc, const void* p, int inner, int outer, int box_rows) {
  CUtensorMap m;
  cuuint64_t dims[2] = {(cuuint64_t)inner, (cuuint64_t)outer};
  cuuint64_t st[1] = {(cuuint64_t)inner * 2};
  cuuint32_t box[2] = {64u, (cuuint32_t)box_rows};
  cuuint32_t es[2] = {1, 1};
  enc(&m, CU_TENSOR_MAP_DATA_TYPE_BFLOAT16, 2, const_cast<void*>(p), dims, st, box, es, CU_TENSOR_MAP_INTERLEAVE_NONE,
      CU_TENSOR_MAP_SWIZZLE_128B, CU_TENSOR_MAP_L2_PROMOTION_L2_128B, CU_TENSOR_MAP_FLOAT_OOB_FILL_NONE);
  return m;
}

__global__ void probe_kernel() {}
bool place_tpcs(int* slot) {
  int dev = 0, sms = 0, fit[17] = {};
  cudaGetDevice(&dev);
  cudaDeviceGetAttribute(&sms, cudaDevAttrMultiProcessorCount, dev);
  if (sms != NCTA) return false;
  cudaFuncSetAttribute(probe_kernel, cudaFuncAttributeMaxDynamicSharedMemorySize, SMEM_BYTES);
  cudaFuncSetAttribute(probe_kernel, cudaFuncAttributeNonPortableClusterSizeAllowed, 1);
  for (int c = 2; c <= 16; c++) {
    cudaLaunchConfig_t cfg = {};
    cudaLaunchAttribute at;
    at.id = cudaLaunchAttributeClusterDimension;
    at.val.clusterDim.x = c; at.val.clusterDim.y = 1; at.val.clusterDim.z = 1;
    cfg.gridDim = dim3(c); cfg.blockDim = dim3(32); cfg.dynamicSmemBytes = SMEM_BYTES; cfg.attrs = &at; cfg.numAttrs = 1;
    if (cudaOccupancyMaxActiveClusters(&fit[c], probe_kernel, &cfg) != cudaSuccess) {
      (void)cudaGetLastError();
      return false;
    }
  }
  int num[10] = {}, size[66], ng = 0;
  num[9] = fit[9] - fit[10];
  for (int t = 8; t >= 1; t--) {
    num[t] = fit[2 * t];
    for (int u = t + 1; u <= 9; u++) num[t] -= num[u] * (u / t);
  }
  for (int t = 1; t <= 9; t++)
    if (num[t] < 0 || num[t] > 66) return false;
  if (fit[2] != 66) return false;
  for (int t = 2; t <= 9; t++)
    for (int i = 0; i < num[t]; i++) size[ng++] = t;
  int first[67], tpc = 0;
  first[ng] = 0;
  for (int g = ng - 1; g >= 0; g--) first[g] = first[g + 1] + (size[g] < 8 ? size[g] : 8);
  int extra = first[0] + num[1];
  for (int r = 0; r < 9; r++)
    for (int g = 0; g < ng; g++)
      if (size[g] > r) slot[tpc++] = r < 8 ? first[g + 1] + r : extra++;
  for (int i = first[0]; tpc < 66;) slot[tpc++] = i++;
  return true;
}

}

extern "C" void kernel_launch(void* const* d_in, const int* in_sizes, int n_in, void* d_out, int out_size) {
  (void)in_sizes; (void)n_in; (void)out_size;
  static EncodeFn enc = nullptr;
  static void* scr = nullptr;
  static bool by_sm = false;
  static int slot[66];
  if (!enc) {
    void* fn = nullptr;
    cudaDriverEntryPointQueryResult q;
    cudaGetDriverEntryPoint("cuTensorMapEncodeTiled", &fn, cudaEnableDefault, &q);
    enc = (EncodeFn)fn;
    cudaGetSymbolAddress(&scr, g_scr);
    cudaFuncSetAttribute(fused_kernel<true>, cudaFuncAttributeMaxDynamicSharedMemorySize, SMEM_BYTES);
    cudaFuncSetAttribute(fused_kernel<false>, cudaFuncAttributeMaxDynamicSharedMemorySize, SMEM_BYTES);
    by_sm = place_tpcs(slot);
  }
  Params P;
  P.x = (const __nv_bfloat16*)d_in[0];
  P.wr = (const __nv_bfloat16*)d_in[1];
  P.wi = (const __nv_bfloat16*)d_in[2];
  P.b1 = (const __nv_bfloat16*)d_in[5];
  P.b2 = (const __nv_bfloat16*)d_in[7];
  P.scr = (unsigned char*)scr;
  P.out = d_out;
  P.zero = 0;
  const int order[14] = {0, 8, 1, 9, 2, 10, 3, 11, 4, 12, 5, 13, 6, 7};
  for (int i = 0; i < NCTA; i++) {
    const int b = by_sm ? 2 * slot[i >> 1] + (i & 1) : i, idx = (b & 15) * 7 + (b >> 4);
    const int pb = b < 112 ? order[idx >> 3] * 8 + (idx & 7) : b & 127;
    P.tab[i] = b | ((pb & 0x78) << 14) | ((pb & 7) << 12);
  }
  const CUtensorMap mW1 = make_map(enc, d_in[4], FF, SEQ, 64);
  const CUtensorMap mW2 = make_map(enc, d_in[6], SEQ, FF, 64);
  const CUtensorMap mX1 = make_map(enc, P.scr + G_X1, 8192, 129, 32);
  if (by_sm) fused_kernel<true><<<NCTA, NTHR, SMEM_BYTES, cudaStreamPerThread>>>(P, mW1, mW2, mX1);
  else fused_kernel<false><<<NCTA - 2, NTHR, SMEM_BYTES, cudaStreamPerThread>>>(P, mW1, mW2, mX1);
}
```

```cpp
#include <cuda_runtime.h>
#include <cuda_bf16.h>
#include <cuda.h>
#include <stdint.h>

constexpr int X1_DT = 500;
constexpr int TM = 3;
constexpr int ZK = 8;
constexpr int ZST = 2;
constexpr int GZ = 11;
constexpr int H_LATE = 2;
constexpr int PF_T = 6000;
constexpr int PF_0 = 2;
constexpr int PF_N = 5;
constexpr int X_ST = 80;

namespace {

constexpr int SEQ = 2048, DM = 512, FF = 1792, DF = 257;
constexpr int NCTA = 132;
constexpr int NTHR = 512;
constexpr int SLOT = 16384;
constexpr int NS = 6, STAGE = 2 * SLOT;
constexpr int S2 = 10 * SLOT, S3 = 11 * SLOT, S0 = 12 * SLOT, S1 = 13 * SLOT;
constexpr int WCH = 33024;
constexpr int XTRA = 14 * SLOT;
constexpr int MISC = 14 * SLOT + 128;
constexpr int BIAS = 14 * SLOT + 512;
constexpr int WHO = 14 * SLOT + 1008;
constexpr int RMAT = 14 * SLOT + 1024;
constexpr int SMEM_BYTES = RMAT + 2048;

constexpr int B_FULL = 0, B_EMPTY = NS, B_S4 = B_EMPTY + 5, B_NONE = 2 * NS, B_WCH = 13, B_WDONE = 17,
              B_STG = 18, B_CF = 19, B_XFREE1 = 20, B_S1 = 21, B_XFREE2 = 22, B_Z = 23, B_FIN = 24,
              B_WQ = 25, B_XFULL1 = 26, B_XFULL2 = 30, B_COUNT = 34;
constexpr int NB_H = 1, NB_U = 2, NB_Z = 3, NB_C = 4, NB_HLP = 5, NB_R = 6, NB_S = 7, NB_T = 8;

constexpr int G_H = 0;
constexpr int G_U = G_H + 128 * SLOT;
constexpr int G_Z = G_U + 112 * SLOT;
constexpr int G_S = G_Z + 128 * SLOT;
constexpr int G_X1 = G_S + 128 * SLOT;
constexpr int G_WT = G_X1 + 129 * SLOT;
constexpr int G_CNT = G_WT + DF * SEQ * 4;
constexpr int C_H = 0, C_X = 2, C_W = 3, C_Z = 4, C_EPOCH = 5, C_U = 6, C_S = 14, C_COUNT = 30;
__device__ __align__(1024) unsigned char g_scr[G_CNT + C_COUNT * 128];

__device__ __forceinline__ void mbar_init(uint32_t b, int c) {
  asm volatile("mbarrier.init.shared::cta.b64 [%0], %1;" ::"r"(b), "r"(c) : "memory");
}
__device__ __forceinline__ void mbar_expect(uint32_t b, int bytes) {
  asm volatile("mbarrier.arrive.expect_tx.shared::cta.b64 _, [%0], %1;" ::"r"(b), "r"(bytes) : "memory");
}
__device__ __forceinline__ void mbar_arrive(uint32_t b) {
  asm volatile("mbarrier.arrive.shared::cta.b64 _, [%0];" ::"r"(b) : "memory");
}
__device__ __forceinline__ void mbar_arrive_cluster(uint32_t remote) {
  asm volatile("mbarrier.arrive.shared::cluster.b64 _, [%0];" ::"r"(remote) : "memory");
}
__device__ __forceinline__ void mbar_wait(uint32_t b, int ph = 0) {
  asm volatile("{\n.reg .pred p;\n.reg .u32 n;\n"
               "mbarrier.try_wait.parity.shared::cta.b64 p, [%0], %1;\n@p bra WD;\n"
               "mov.u32 n, 0;\nWL:\n"
               "mbarrier.try_wait.parity.shared::cta.b64 p, [%0], %1, 4000;\n@p bra WD;\n"
               "add.u32 n, n, 1;\nsetp.lt.u32 p, n, 0x20000;\n@p bra WL;\ntrap;\nWD:\n}" ::"r"(b), "r"(ph) : "memory");
}
__device__ __forceinline__ bool mbar_test(uint32_t b) {
  uint32_t ok;
  asm volatile("{\n.reg .pred p;\nmbarrier.test_wait.parity.shared::cta.b64 p, [%1], 0;\nselp.u32 %0, 1, 0, p;\n}" : "=r"(ok) : "r"(b) : "memory");
  return ok;
}
__device__ __forceinline__ bool elect_one() {
  uint32_t p;
  asm volatile("{\n.reg .pred e;\nelect.sync _|e, 0xffffffff;\nselp.u32 %0, 1, 0, e;\n}" : "=r"(p));
  return p;
}
__device__ __forceinline__ uint32_t mapa(uint32_t a, uint32_t cta) {
  uint32_t r;
  asm("mapa.shared::cluster.u32 %0, %1, %2;" : "=r"(r) : "r"(a), "r"(cta));
  return r;
}
__device__ __forceinline__ void tma2d(uint32_t dst, const CUtensorMap* m, int c0, int c1, uint32_t bar) {
  asm volatile("cp.async.bulk.tensor.2d.shared::cluster.global.mbarrier::complete_tx::bytes [%0], [%1, {%3, %4}], [%2];"
               ::"r"(dst), "l"(m), "r"(bar), "r"(c0), "r"(c1) : "memory");
}
__device__ __forceinline__ void tma2d_store(const CUtensorMap* m, int c0, int c1, uint32_t src) {
  asm volatile("cp.async.bulk.tensor.2d.global.shared::cta.bulk_group [%0, {%2, %3}], [%1];"
               ::"l"(m), "r"(src), "r"(c0), "r"(c1) : "memory");
}
__device__ __forceinline__ void bulk_load(uint32_t dst, const void* src, int bytes, uint32_t bar) {
  asm volatile("cp.async.bulk.shared::cluster.global.mbarrier::complete_tx::bytes [%0], [%1], %2, [%3];"
               ::"r"(dst), "l"(src), "r"(bytes), "r"(bar) : "memory");
}
__device__ __forceinline__ void bulk_store(void* dst, uint32_t src, int bytes) {
  asm volatile("cp.async.bulk.global.shared::cta.bulk_group [%0], [%1], %2;" ::"l"(dst), "r"(src), "r"(bytes) : "memory");
}
__device__ __forceinline__ void bulk_commit() { asm volatile("cp.async.bulk.commit_group;" ::: "memory"); }
__device__ __forceinline__ void bulk_wait_all() { asm volatile("cp.async.bulk.wait_group 0;" ::: "memory"); }
__device__ __forceinline__ void fence_async_smem() { asm volatile("fence.proxy.async.shared::cta;" ::: "memory"); }
__device__ __forceinline__ void prefetch_map(const CUtensorMap* m) {
  asm volatile("prefetch.tensormap [%0];" ::"l"(m) : "memory");
}
__device__ __forceinline__ void nb_sync(int id, int n) { asm volatile("bar.sync %0, %1;" ::"r"(id), "r"(n) : "memory"); }
__device__ __forceinline__ void nb_arrive(int id, int n) { asm volatile("bar.arrive %0, %1;" ::"r"(id), "r"(n) : "memory"); }
__device__ __forceinline__ void signal(const void* cnt, unsigned inc) {
  asm volatile("fence.proxy.async;\nred.relaxed.gpu.global.add.u32 [%0], %1;" ::"l"(cnt), "r"(inc) : "memory");
}
__device__ __forceinline__ unsigned ld_relaxed(const void* p) {
  unsigned v;
  asm volatile("ld.relaxed.gpu.global.u32 %0, [%1];" : "=r"(v) : "l"(p) : "memory");
  return v;
}
__device__ __forceinline__ void poll(const void* cnt, unsigned base, unsigned mask, unsigned& seen) {
  asm volatile("{\n.reg .pred p;\n.reg .u32 n, v;\nand.b32 v, %0, %3;\nsetp.ne.u32 p, v, 0;\n@p bra PD;\nmov.u32 n, 0;\nPL:\n"
               "ld.acquire.gpu.global.u32 v, [%1];\nsub.u32 %0, v, %2;\nand.b32 v, %0, %3;\nsetp.ne.u32 p, v, 0;\n@p bra PD;\n"
               "add.u32 n, n, 1;\nsetp.lt.u32 p, n, 0x200000;\n@p bra PL;\ntrap;\nPD:\n}"
               : "+r"(seen) : "l"(cnt), "r"(base), "r"(mask) : "memory");
}
__device__ __forceinline__ void poll(const void* cnt, unsigned base, unsigned mask) {
  unsigned seen = 0;
  poll(cnt, base, mask, seen);
}
__device__ __forceinline__ void stg32(void* p, uint32_t a) { asm volatile("st.global.u32 [%0], %1;" ::"l"(p), "r"(a) : "memory"); }
__device__ __forceinline__ void stg64(void* p, uint32_t a, uint32_t b) {
  asm volatile("st.global.v2.u32 [%0], {%1,%2};" ::"l"(p), "r"(a), "r"(b) : "memory");
}
__device__ __forceinline__ uint32_t pack(float lo, float hi) {
  uint32_t r;
  asm("cvt.rn.bf16x2.f32 %0, %1, %2;" : "=r"(r) : "f"(hi), "f"(lo));
  return r;
}
__device__ __forceinline__ float blo(uint32_t v) { return __uint_as_float(v << 16); }
__device__ __forceinline__ float bhi(uint32_t v) { return __uint_as_float(v & 0xffff0000u); }
__device__ __forceinline__ uint32_t hfma2(uint32_t a, uint32_t b, uint32_t c) {
  uint32_t r;
  asm("fma.rn.bf16x2 %0, %1, %2, %3;" : "=r"(r) : "r"(a), "r"(b), "r"(c));
  return r;
}
__device__ __forceinline__ float rsqrt_fast(float x) {
  float r;
  asm("rsqrt.approx.f32 %0, %1;" : "=f"(r) : "f"(x));
  return r;
}
__device__ __forceinline__ float tanh_fast(float x) {
  float r;
  asm("tanh.approx.f32 %0, %1;" : "=f"(r) : "f"(x));
  return r;
}
__device__ __forceinline__ uint32_t movm(uint32_t a) {
  uint32_t d;
  asm("movmatrix.sync.aligned.m8n8.trans.b16 %0, %1;" : "=r"(d) : "r"(a));
  return d;
}
__device__ __forceinline__ void stsm4(uint32_t a, uint32_t r0, uint32_t r1, uint32_t r2, uint32_t r3) {
  asm volatile("stmatrix.sync.aligned.m8n8.x4.shared.b16 [%0], {%1,%2,%3,%4};" ::"r"(a), "r"(r0), "r"(r1), "r"(r2), "r"(r3) : "memory");
}
__device__ __forceinline__ void ldsm4t(uint32_t a, uint32_t* r) {
  asm volatile("ldmatrix.sync.aligned.m8n8.x4.trans.shared.b16 {%0,%1,%2,%3}, [%4];"
               : "=r"(r[0]), "=r"(r[1]), "=r"(r[2]), "=r"(r[3]) : "r"(a) : "memory");
}
__device__ __forceinline__ void st_async4(uint32_t a, uint32_t r0, uint32_t r1, uint32_t r2, uint32_t r3, uint32_t bar) {
  asm volatile("st.async.weak.shared::cluster.mbarrier::complete_tx::bytes.v4.b32 [%0], {%1,%2,%3,%4}, [%5];"
               ::"r"(a), "r"(r0), "r"(r1), "r"(r2), "r"(r3), "r"(bar) : "memory");
}
__device__ __forceinline__ uint4 lds128(uint32_t a) {
  uint4 v;
  asm volatile("ld.shared.v4.u32 {%0,%1,%2,%3}, [%4];" : "=r"(v.x), "=r"(v.y), "=r"(v.z), "=r"(v.w) : "r"(a) : "memory");
  return v;
}
__device__ __forceinline__ uint32_t lds32(uint32_t a) {
  uint32_t v;
  asm volatile("ld.shared.u32 %0, [%1];" : "=r"(v) : "r"(a) : "memory");
  return v;
}
__device__ __forceinline__ uint32_t clk() {
  uint32_t c;
  asm volatile("mov.u32 %0, %%clock;" : "=r"(c));
  return c;
}
__device__ __forceinline__ void wait_until(uint32_t t0, int dt) {
  while ((int)(clk() - t0) < dt) {}
}
__device__ __forceinline__ uint32_t dlo(uint32_t addr, uint32_t lbo) { return ((addr & 0x3FFFF) >> 4) | ((lbo >> 4) << 16); }
__host__ __device__ constexpr uint32_t dhi(uint32_t sbo, uint32_t sw) { return (sbo >> 4) | (sw << 30); }
__device__ __forceinline__ void wg_fence() { asm volatile("wgmma.fence.sync.aligned;" ::: "memory"); }
__device__ __forceinline__ void wg_commit() { asm volatile("wgmma.commit_group.sync.aligned;" ::: "memory"); }
template <int N> __device__ __forceinline__ void wg_wait() { asm volatile("wgmma.wait_group.sync.aligned %0;" ::"n"(N) : "memory"); }
template <int N> __device__ __forceinline__ void keep(float* d) {
#pragma unroll
  for (int i = 0; i < N; i++) asm volatile("" : "+f"(d[i])::"memory");
}
template <int N> __device__ __forceinline__ void renew(float* d) {
#pragma unroll
  for (int i = 0; i < N; i++) asm volatile("mov.b32 %0, %1;" : "=f"(d[i]) : "f"(d[i]) : "memory");
}
template <int N> __device__ __forceinline__ void pin(const void* v, uint32_t zero) {
  const uint32_t* d = (const uint32_t*)v;
  uint32_t x = 0;
#pragma unroll
  for (int i = 0; i < N; i++) x ^= d[i];
  asm volatile("{\n.reg .pred p;\nsetp.ne.u32 p, %1, 0;\n@p st.shared.b32 [%1], %0;\n}" ::"r"(x), "r"(zero) : "memory");
}
__device__ __forceinline__ float after_here(float v, uint32_t zero) {
  uint32_t r = __float_as_uint(v);
  asm volatile("{\n.reg .pred p;\n.reg .u32 n;\nmov.u32 n, %1;\nSF:\nadd.u32 %0, %0, n;\nsetp.ne.u32 p, n, 0;\nshr.u32 n, n, 1;\n@p bra SF;\n}"
               : "+r"(r) : "r"(zero) : "memory");
  return __uint_as_float(r);
}
template <int N> __device__ __forceinline__ void keepu(uint32_t* d) {
#pragma unroll
  for (int i = 0; i < N; i++) asm volatile("" : "+r"(d[i])::"memory");
}
#define R8(c, o) c(d[o]), c(d[o + 1]), c(d[o + 2]), c(d[o + 3]), c(d[o + 4]), c(d[o + 5]), c(d[o + 6]), c(d[o + 7])
#define D32 "%0,%1,%2,%3,%4,%5,%6,%7,%8,%9,%10,%11,%12,%13,%14,%15,%16,%17,%18,%19,%20,%21,%22,%23,%24,%25,%26,%27,%28,%29,%30,%31"
#define D64 D32 ",%32,%33,%34,%35,%36,%37,%38,%39,%40,%41,%42,%43,%44,%45,%46,%47,%48,%49,%50,%51,%52,%53,%54,%55,%56,%57,%58,%59,%60,%61,%62,%63"
template <int TB> __device__ __forceinline__ void wgmma128(float* d, uint32_t a, uint32_t b, int accum) {
  asm volatile("{\n.reg .b64 da, db;\n.reg .pred p;\nsetp.ne.b32 p, %69, 0;\nmov.b64 da, {%64, %67};\nmov.b64 db, {%65, %68};\n"
               "wgmma.mma_async.sync.aligned.m64n128k16.f32.bf16.bf16 {" D64 "}, da, db, p, 1, 1, 1, %66;\n}"
               : R8("+f", 0), R8("+f", 8), R8("+f", 16), R8("+f", 24), R8("+f", 32), R8("+f", 40), R8("+f", 48), R8("+f", 56)
               : "r"(a), "r"(b), "n"(TB), "n"(dhi(1024, 1)), "n"(dhi(1024, TB)), "r"(accum));
}
template <int ACC, int TB, int SBO, int SW = 0>
__device__ __forceinline__ void wgmma64rs(float* d, const uint32_t* a, uint32_t b) {
  asm volatile("{\n.reg .b64 db;\nmov.b64 db, {%36, %39};\n"
               "wgmma.mma_async.sync.aligned.m64n64k16.f32.bf16.bf16 {" D32 "}, {%32,%33,%34,%35}, db, %37, 1, 1, %38;\n}"
               : R8("+f", 0), R8("+f", 8), R8("+f", 16), R8("+f", 24)
               : "r"(a[0]), "r"(a[1]), "r"(a[2]), "r"(a[3]), "r"(b), "n"(ACC), "n"(TB), "n"(dhi(SBO, SW)));
}
template <int ACC, int TB, int SBO>
__device__ __forceinline__ void wgmma32rs(float* d, const uint32_t* a, uint32_t b) {
  asm volatile("{\n.reg .b64 db;\nmov.b64 db, {%20, %23};\n"
               "wgmma.mma_async.sync.aligned.m64n32k16.f32.bf16.bf16 {%0,%1,%2,%3,%4,%5,%6,%7,%8,%9,%10,%11,%12,%13,%14,%15}, "
               "{%16,%17,%18,%19}, db, %21, 1, 1, %22;\n}"
               : R8("+f", 0), R8("+f", 8)
               : "r"(a[0]), "r"(a[1]), "r"(a[2]), "r"(a[3]), "r"(b), "n"(ACC), "n"(TB), "n"(dhi(SBO, 0)));
}

struct RowConst { float c[2][4], s[2][4]; };
__device__ __forceinline__ void rot(float& c, float& s, float dc, float ds) {
  const float n = c * dc - s * ds;
  s = s * dc + c * ds;
  c = n;
}
__device__ __forceinline__ void row_const(RowConst& r, int lane) {
  const int g = lane >> 2, t = lane & 3;
#pragma unroll
  for (int h = 0; h < 2; h++) {
    const float w = (float)(2 * g + h) * 0.02454369260617026f;
    float c, s, dc, ds;
    __sincosf(w * (float)(4 * t), &s, &c);
    __sincosf(w, &ds, &dc);
#pragma unroll
    for (int k = 0; k < 4; k++) {
      r.c[h][2 * (k & 1) + (k >> 1)] = c; r.s[h][2 * (k & 1) + (k >> 1)] = s;
      if (k < 3) rot(c, s, dc, ds);
    }
  }
}
template <int NR> __device__ __forceinline__ void row_step1(uint32_t sb, const uint32_t (*a)[8], float (*z)[16]) {
  const uint32_t d = dlo(sb + RMAT, 128);
#pragma unroll
  for (int r = 0; r < NR; r++) {
    wgmma32rs<0, 0, 512>(z[r], a[r], d);
    wgmma32rs<1, 0, 512>(z[r], a[r] + 4, d + (256 >> 4));
  }
  wg_commit();
}
template <int NR> __device__ __forceinline__ void row_twiddle(const RowConst& rc, uint32_t (*a)[8], float (*z)[16]) {
#pragma unroll
  for (int r = 0; r < NR; r++) {
    keep<16>(z[r]);
#pragma unroll
    for (int h = 0; h < 2; h++)
#pragma unroll
      for (int u = 0; u < 2; u++) {
        const float r0 = z[r][8 * u + 2 * h], r1 = z[r][8 * u + 2 * h + 1], i0 = z[r][8 * u + 4 + 2 * h], i1 = z[r][8 * u + 5 + 2 * h];
        const float c0 = rc.c[h][2 * u], s0 = rc.s[h][2 * u], c1 = rc.c[h][2 * u + 1], s1 = rc.s[h][2 * u + 1];
        a[r][4 * h + u] = movm(pack(i0 * c0 - r0 * s0, i1 * c1 - r1 * s1));
        a[r][4 * h + 2 + u] = movm(pack(r0 * c0 + i0 * s0, r1 * c1 + i1 * s1));
      }
    keepu<8>(a[r]);
  }
}
template <int NR> __device__ __forceinline__ void row_step2(uint32_t sb, const uint32_t (*a)[8], float (*z)[16]) {
  const uint32_t d = dlo(sb + RMAT, 512);
#pragma unroll
  for (int r = 0; r < NR; r++) {
    wgmma32rs<0, 1, 128>(z[r], a[r], d);
    wgmma32rs<1, 1, 128>(z[r], a[r] + 4, d + (1024 >> 4));
  }
  wg_commit();
}

struct Params {
  const __nv_bfloat16* x;
  unsigned char* scr;
  void* out;
  uint32_t zero;
  uint32_t tab[132];
  const __nv_bfloat16 *wr, *wi, *w2, *b1, *b2;
};

template <int NR>
__device__ __forceinline__ void row_ifft(const RowConst& rc, uint32_t sb, unsigned char* scr, int b, int lane, int q, int i0) {
  const int g = lane >> 2, t = lane & 3;
  const int col = t >> 1;
  uint32_t za[2], A[NR][8];
#pragma unroll
  for (int h = 0; h < 2; h++) {
    const int kl = 16 * (t & 1) + 2 * g + h, p = col ? 128 - kl : kl;
    za[h] = sb + S0 + p * 128 + (((4 * q + i0) ^ ((p >> 1) & 15)) << 3) + col * 4;
  }
  const int stp = col ? -4096 : 4096;
  float z[NR][16];
  mbar_wait(sb + MISC + 8 * B_Z);
#pragma unroll
  for (int r = 0; r < NR; r++)
#pragma unroll
    for (int j = 0; j < 8; j++)
      A[r][j] = lds32((j ? za[j & 1] + (j >> 1) * stp : lane == 2 ? za[0] - SLOT : za[0]) ^ (r << 3));
  wg_fence();
  row_step1<NR>(sb, A, z);
  wg_wait<0>();
  row_twiddle<NR>(rc, A, z);
  wg_fence();
  row_step2<NR>(sb, A, z);
  unsigned char* sp = scr + G_S + ((b >> 3) * 128 + 32 * i0 + 4 * (b & 7) + q) * 1024 + col * 512 + (t & 1) * 64 + g * 8;
  wg_wait<0>();
#pragma unroll
  for (int r = 0; r < NR; r++) {
    keep<16>(z[r]);
#pragma unroll
    for (int j = 0; j < 4; j++)
      stg64(sp + r * 32768 + j * 128, pack(z[r][4 * j], z[r][4 * j + 1]), pack(z[r][4 * j + 2], z[r][4 * j + 3]));
  }
  nb_arrive(NB_S, 288);
}

__device__ __forceinline__ void transpose_w(uint32_t sb, unsigned char* scr, int b, int ht) {
#pragma unroll 1
  for (int ch = 0; ch < 4; ch++) {
    unsigned char* wp = scr + G_WT + (ht >> 3) * 8192 + (b - 112) * 512 + ch * 128 +
                        (((ht & 7) * 16) ^ (((b & 1) * 2 + (ch >> 1)) << 5));
    uint32_t a = sb + ch * WCH + (4 * (ht & 7) * DF + (ht >> 3)) * 2;
    mbar_wait(sb + MISC + 8 * (B_WCH + ch));
#pragma unroll 1
    for (int n0 = 0; n0 < 18; n0 += 3) {
      uint32_t e[3][8];
#pragma unroll
      for (int n = 0; n < 3; n++)
#pragma unroll
        for (int i = 0; i < 8; i++)
          asm volatile("ld.shared.u16 %0, [%1];" : "=r"(e[n][i]) : "r"(a + n * 32 + (i >> 1) * DF * 2 + (i & 1) * 16448) : "memory");
#pragma unroll
      for (int n = 0; n < 3; n++)
        if (16 * (n0 + n) + (ht >> 3) < DF)
          asm volatile("st.global.v4.u32 [%0], {%1,%2,%3,%4};" ::"l"(wp + n * 16 * 8192),
                       "r"(__byte_perm(e[n][0], e[n][1], 0x5410)), "r"(__byte_perm(e[n][2], e[n][3], 0x5410)),
                       "r"(__byte_perm(e[n][4], e[n][5], 0x5410)), "r"(__byte_perm(e[n][6], e[n][7], 0x5410)) : "memory");
      a += 96;
      wp += 48 * 8192;
    }
  }
}

struct Ring {
  uint32_t s, ph;
  __device__ __forceinline__ void next() { if (++s == NS - 1) { s = 0; ph ^= 1; } }
};

struct Gemm {
  Ring r;
  uint32_t prev;
  uint32_t dA, dB, bars;
  uint32_t zr;
  bool lead;
  template <int TB, int KSTEP, int TAIL = 0>
  __device__ __forceinline__ void run(float* acc, int n, int accum) {
#pragma unroll 1
    for (int i = 0; i < n; i++) {
      mbar_wait(bars + 8 * r.s, r.ph);
      const uint32_t a = dA + r.s * (STAGE >> 4), w = dB + r.s * (STAGE >> 4);
      wg_fence();
#pragma unroll
      for (int k = 0; k < 4; k++) {
        wgmma128<TB>(acc, a + k * 128, w + k * KSTEP, k ? 1 : accum);
        if (k == TAIL) {
          wg_commit();
          wg_wait<1>();
          if (lead) mbar_arrive(prev);
          wg_fence();
        }
      }
      wg_commit();
      accum = 1;
      prev = bars + 8 * (B_EMPTY + r.s);
      r.next();
      if (!TB && TAIL && i == n - 2) r = {NS - 1, 0};
    }
  }
  __device__ __forceinline__ void drain() {
    wg_wait<0>();
    if (lead) mbar_arrive(prev);
    prev = bars + 8 * B_NONE;
  }
  template <int TB, int KSTEP, class F>
  __device__ __forceinline__ void tail(float* acc, int wg, F&& pre, uint32_t lda, uint32_t bias, uint32_t xdst, uint32_t xfull, int xfree) {
    constexpr int T = TM;
    uint32_t bb[8];
    auto prepare = [&]() {
      pre();
      mbar_wait(bars + 8 * xfree);
      if (TB) {
#pragma unroll
        for (int j = 0; j < 8; j++) bb[j] = lds32(bias + 16 * j);
      } else {
#pragma unroll
        for (int h = 0; h < 2; h++) asm volatile("ld.shared.u16 %0, [%1];" : "=r"(bb[h]) : "r"(bias + 16 * h) : "memory");
      }
    };
    auto send = [&](int j) {
      const float* a = acc + 32 + 16 * (j & 1) + (j & 2);
      st_async4(xdst + j * 4096, pack(a[0], a[1]), pack(a[4], a[5]), pack(a[8], a[9]), pack(a[12], a[13]), xfull + 4 * (j & 2));
    };
    if (TB && wg) {
      drain();
      renew<64>(acc);
      uint32_t A[T][16], w[T], em[T];
#pragma unroll
      for (int i = 0; i < T; i++) {
        mbar_wait(bars + 8 * r.s, r.ph);
#pragma unroll
        for (int k = 0; k < 4; k++) ldsm4t(lda + r.s * STAGE + k * 2048, A[i] + 4 * k);
        w[i] = dB + r.s * (STAGE >> 4);
        em[i] = bars + 8 * (B_EMPTY + r.s);
        r.next();
      }
      prepare();
      nb_sync(NB_T, 256);
      wg_fence();
#pragma unroll
      for (int n = 0; n < 4 * T; n++) wgmma64rs<1, TB, 1024, TB>(acc + 32, A[n >> 2] + 4 * (n & 3), w[n >> 2] + 512 + (n & 3) * KSTEP);
      wg_commit();
#pragma unroll
      for (int n = 0; n < 4 * T; n++) {
        wgmma64rs<1, TB, 1024, TB>(acc, A[n >> 2] + 4 * (n & 3), w[n >> 2] + (n & 3) * KSTEP);
        if (n == 3) { wg_commit(); wg_wait<1>(); keep<32>(acc + 32); send(0); wg_fence(); }
        if (n > 3 && n < 7) send(n - 3);
      }
      wg_commit();
      wg_wait<0>();
      keep<32>(acc);
      if (lead) {
#pragma unroll
        for (int i = 0; i < T; i++) mbar_arrive(em[i]);
      }
    } else {
      if (wg) { drain(); nb_sync(NB_T, 256); }
      run<TB, KSTEP, 1>(acc, T, 1);
      if (!wg) nb_arrive(NB_T, 256);
      prepare();
      drain();
      keep<64>(acc);
#pragma unroll
      for (int j = 0; j < 4; j++) send(j);
      if (TB) renew<32>(acc);
    }
    const float half = after_here(0.5f, zr);
#pragma unroll
    for (int j = 0; j < 32; j++)
      acc[j] = fmaf(acc[j], half, half * (TB ? ((j & 1) ? bhi(bb[j >> 2]) : blo(bb[j >> 2])) : blo(bb[(j >> 1) & 1])));
    pin<32>(acc, zr);
  }
};

template <bool BY_SM>
__global__ void __cluster_dims__(2, 1, 1) __launch_bounds__(NTHR, 1)
fused_kernel(const __grid_constant__ Params P, const __grid_constant__ CUtensorMap mW1, const __grid_constant__ CUtensorMap mW2,
             const __grid_constant__ CUtensorMap mX1) {
  extern __shared__ __align__(1024) unsigned char smem[];
#define GET_B uint32_t sm_, rk_;                                                                         \
  if (BY_SM) asm volatile("mov.u32 %0, %%smid;" : "=r"(sm_));                                            \
  else asm volatile("mov.u32 %0, %%ctaid.x;" : "=r"(sm_));                                                       \
  asm volatile("mov.u32 %0, %%cluster_ctarank;" : "=r"(rk_));                                            \
  const uint32_t tb_ = P.tab[(sm_ & ~1u) | rk_];                                                         \
  const int b = tb_ & 255, pb = ((tb_ >> 14) & 0x78) | ((tb_ >> 12) & 7);
#define cnt(c) (scr + G_CNT + 128 * (c))
#define ROLE_CTX                                                                                         \
  const uint32_t sb = __shfl_sync(0xffffffffu, (uint32_t)__cvta_generic_to_shared(smem), 0);             \
  int tid;                                                                                               \
  GET_B                                                                                                  \
  asm volatile("mov.u32 %0, %%tid.x;" : "=r"(tid));                                                      \
  const int lane = tid & 31, warp = __shfl_sync(0xffffffffu, tid >> 5, 0);                               \
  const bool main_cta = b < 128, g1_cta = b < 112;                                                       \
  const int rank = b & 1, dt = (b >> 1) & 3, wt = b >> 3;                                  \
  unsigned char* const scr = P.scr;                                                                      \
  auto bar = [&](int i) { return sb + MISC + 8 * i; };                                                   \
  (void)rank; (void)dt; (void)wt; (void)lane; (void)warp; (void)g1_cta; (void)pb;
  uint32_t L[2][8];
  {
    const uint32_t tx = threadIdx.x;
    const unsigned char* xp = (const unsigned char*)P.x + ((tx & 32) * 2048 + (tx >> 6) * 1024 + (tx & 2) * 256 + (tx & 1) * 64 + (tx & 28) * 2);
    GET_B
    (void)b; (void)pb;
    xp += tb_ & 0x1ff000;
    if (tx < 256 && (tb_ >> 21)) wait_until(clk(), tb_ >> 21);
    const uint32_t on = tx < 256;
#pragma unroll
    for (int i = 0; i < 8; i++)
      asm volatile("{\n.reg .pred p;\nsetp.ne.u32 p, %3, 0;\n@p ld.global.nc.v2.u32 {%0,%1}, [%2];\n}"
                   : "=r"(L[i >> 2][2 * (i & 3)]), "=r"(L[i >> 2][2 * (i & 3) + 1]) : "l"(xp + (i >> 2) * 32768 + (i & 3) * 128), "r"(on));
  }
  if (threadIdx.x < 256) {
    asm volatile("barrier.cluster.arrive.relaxed.aligned;" ::: "memory");
    asm volatile("setmaxnreg.inc.sync.aligned.u32 208;");
    ROLE_CTX
    if (b > 128) return;
    const int g = lane >> 2, t = lane & 3, wg = warp >> 2;
    const uint32_t zr = P.zero & tid;
    const int hprio = (pb >> 3) & 7;
    const int pcol = b == 0 ? 128 : (b & 0x70) | ((b & 7) << 1) | ((b >> 3) & 1);
    const int k1c = 8 * warp + g;
    uint32_t fa[8][4];
    auto fa_consts = [&]() {
      float c, s, dc, ds;
      __sincosf((float)(k1c * t) * 0.09817477042468103f, &s, &c);
      __sincosf((float)(k1c & 15) * 0.39269908169872414f, &ds, &dc);
#pragma unroll
      for (int n = 0; n < 8; n++) {
        fa[n >> 1][2 * (n & 1)] = pack(c, s);
        fa[n >> 1][2 * (n & 1) + 1] = pack(-s, c);
        if (n < 7) rot(c, s, dc, ds);
      }
#pragma unroll
      for (int n = 0; n < 16; n++) fa[4 + (n >> 2)][n & 3] = fa[n >> 2][n & 3] ^ ((g & 1) ? 0x80008000u : 0u);
      keepu<16>(fa[4]);
      pin<16>(fa[4], zr);
    };
    RowConst rc;
    uint32_t hq[2][8];
    unsigned char* hp;
    auto store_h = [&]() {
#pragma unroll
      for (int r = 0; r < 2; r++)
#pragma unroll
        for (int j = 0; j < 4; j++) stg64(hp + r * 4096 + (j >> 1) * 32 * SLOT + (j & 1) * 8192, hq[r][2 * j], hq[r][2 * j + 1]);
      nb_arrive(NB_H, 288);
    };
    if (main_cta) {
      const int row0 = 128 * (pb >> 3) + 64 * (warp & 1) + 4 * (pb & 7) + (warp >> 1);
      const int col = t >> 1;
      hp = scr + G_H + ((2 * col * 32 + (row0 >> 6)) * 2) * 8192 + (row0 & 63) * 128 +
                          (((4 * (t & 1) + (g >> 1)) ^ (row0 & 7)) << 4) + (g & 1) * 8;
      uint32_t sta[4];
      auto row_consts = [&](int lane) {
        const int g = lane >> 2, t = lane & 3, col = t >> 1;
        row_const(rc, lane);
        {
          const uint32_t un = (warp >> 1) * 2 + col, sub = 8 * (warp & 1);
#pragma unroll
          for (int h = 0; h < 2; h++) {
            const int kl = 16 * (t & 1) + 2 * g + h, p = col ? 128 - kl : kl, r7 = (p >> 1) & 7;
            sta[h] = sb + S0 + ((p & 0xf0) + 8 * h + r7) * 128 + ((un ^ r7) << 4) + sub;
          }
          sta[2] = (lane & 29) ? sta[0] : col ? sta[0] - SLOT : sb + XTRA + (un << 4) + sub;
          sta[3] = (uint32_t)(uintptr_t)hp;
        }
        pin<16>(&rc, zr); pin<4>(sta, zr);
      };
      if (hprio >= H_LATE) {
        row_consts(lane);
        fa_consts();
      } else {
        const uint32_t hl = (uint32_t)(uintptr_t)hp;
        pin<1>(&hl, zr);
      }
      float v[2][16], s1[2], s2[2];
#pragma unroll
      for (int r = 0; r < 2; r++) {
        const float piv = blo(__shfl_sync(0xffffffffu, L[r][0], 0));
        s1[r] = 0.f; s2[r] = 0.f;
#pragma unroll
        for (int j = 0; j < 8; j++) { v[r][2 * j] = blo(L[r][j]) - piv; v[r][2 * j + 1] = bhi(L[r][j]) - piv; }
#pragma unroll
        for (int i = 0; i < 16; i++) { s1[r] += v[r][i]; s2[r] = fmaf(v[r][i], v[r][i], s2[r]); }
      }
      {
        const bool hi = lane & 16, q = lane & 8;
        float a = (hi ? s1[1] : s1[0]) + __shfl_xor_sync(0xffffffffu, hi ? s1[0] : s1[1], 16);
        float c = (hi ? s2[1] : s2[0]) + __shfl_xor_sync(0xffffffffu, hi ? s2[0] : s2[1], 16);
        a = (q ? c : a) + __shfl_xor_sync(0xffffffffu, q ? a : c, 8);
#pragma unroll
        for (int o = 4; o > 0; o >>= 1) a += __shfl_xor_sync(0xffffffffu, a, o);
        s1[0] = __shfl_sync(0xffffffffu, a, 0); s2[0] = __shfl_sync(0xffffffffu, a, 8);
        s1[1] = __shfl_sync(0xffffffffu, a, 16); s2[1] = __shfl_sync(0xffffffffu, a, 24);
      }
#pragma unroll
      for (int r = 0; r < 2; r++) {
        s1[r] *= -1.f / DM;
        s2[r] = fmaxf(fmaf(-s1[r], s1[r], s2[r] * (1.f / DM)), 0.f);
        const float a2 = rsqrt_fast(fmaf(s2[r], 1.f + 1e-5f, 1e-10f)), c2 = s1[r] * a2;
#pragma unroll
        for (int j = 0; j < 8; j++) hq[r][j] = pack(fmaf(v[r][2 * j], a2, c2), fmaf(v[r][2 * j + 1], a2, c2));
      }
      if (hprio < H_LATE) store_h();
      if (hprio < H_LATE) row_consts(__float_as_uint(after_here(__uint_as_float(lane), zr)));
      nb_sync(NB_R, 384);
      const float eps = after_here(1e-5f, zr);
#pragma unroll
      for (int r = 0; r < 2; r++) {
        const float a1 = rsqrt_fast(s2[r] + eps), c1 = s1[r] * a1;
#pragma unroll
        for (int j = 0; j < 8; j++) L[r][j] = pack(fmaf(v[r][2 * j], a1, c1), fmaf(v[r][2 * j + 1], a1, c1));
      }
      wg_fence();
      row_step1<2>(sb, L, v);
      if (hprio >= H_LATE) store_h();
      wg_wait<0>();
      row_twiddle<2>(rc, L, v);
      wg_fence();
      row_step2<2>(sb, L, v);
      wg_wait<0>();
      keep<16>(v[0]);
      keep<16>(v[1]);
      const uint32_t cj = col << 31;
      const int stp = col ? -4096 : 4096;
#pragma unroll
      for (int j = 0; j < 4; j++)
#pragma unroll
        for (int h = 0; h < 2; h++) {
          const uint32_t a = (j | h) ? sta[h] + j * stp : sta[2];
          const uint32_t z0 = pack(v[0][4 * j + 2 * h + 1], v[0][4 * j + 2 * h]) ^ cj;
          const uint32_t z1 = pack(v[1][4 * j + 2 * h + 1], v[1][4 * j + 2 * h]) ^ cj;
          if (!(j | h) && !(lane & 29))
            asm volatile("st.shared.v2.u32 [%0], {%1,%2};" ::"r"(a ^ 16), "r"(z0 ^ 0x80000000u), "r"(z1 ^ 0x80000000u) : "memory");
          asm volatile("st.shared.v2.u32 [%0], {%1,%2};" ::"r"(a), "r"(z0), "r"(z1) : "memory");
        }
      fence_async_smem();
      __syncwarp();
      if (lane == 0) mbar_arrive(bar(B_STG));
    } else {
      nb_sync(NB_R, 384);
    }
    if (hprio < H_LATE) fa_consts();
    const uint32_t peer = mapa(sb, rank ^ 1);
    float c[32];
    const uint32_t dB1 = dlo(sb + S1, 1024);
    const uint32_t lda = sb + 8192 + ((lane & 7) + 8 * (lane >> 4)) * 128 + (((2 * (warp & 3) + ((lane >> 3) & 1)) ^ (lane & 7)) << 4);
    Gemm gm;
    gm.r = {0, 0}; gm.bars = bar(0); gm.prev = bar(B_NONE); gm.lead = (tid & 127) == 0; gm.zr = zr;
    if (g1_cta) {
      float acc[64];
      gm.dA = dlo(sb + wg * 8192, 8192); gm.dB = dlo(sb + SLOT, 8192);
      gm.run<1, 128>(acc, 16 - TM, 0);
      gm.tail<1, 128>(acc, wg, []() {}, lda, sb + BIAS + 4 * t, peer + S0 + tid * 16, peer + MISC + 8 * B_XFULL1 + 16 * wg, B_XFREE1);
      if (wg) mbar_wait(bar(B_CF));
      unsigned char* up = scr + G_U + (dt * 28 + 2 * wt + rank) * SLOT + warp * 2048 + lane * 4;
#pragma unroll
      for (int h = 0; h < 2; h++) {
        mbar_wait(bar(B_XFULL1 + h) + 16 * wg);
        const uint4 oa = lds128(sb + S0 + tid * 16 + h * 8192), ob = lds128(sb + S0 + tid * 16 + h * 8192 + 4096);
        const uint32_t o[8] = {oa.x, oa.y, oa.z, oa.w, ob.x, ob.y, ob.z, ob.w};
        float y[16], th[16];
#pragma unroll
        for (int i = 0; i < 16; i++) {
          y[i] = fmaf((i & 1) ? bhi(o[i >> 1]) : blo(o[i >> 1]), 0.5f, acc[4 * (i >> 1) + 2 * h + (i & 1)]);
          th[i] = tanh_fast(y[i] * fmaf(y[i] * y[i], 0.285419265090401f, 1.5957691216057308f));
        }
#pragma unroll
        for (int nt = 0; nt < 8; nt++)
          stg32(up + nt * 128 + h * 1024, pack(fmaf(y[2 * nt], th[2 * nt], y[2 * nt]), fmaf(y[2 * nt + 1], th[2 * nt + 1], y[2 * nt + 1])));
      }
      nb_arrive(NB_U, 288);
    } else if (main_cta) {
      mbar_wait(bar(B_XFREE1));
    }
    if (!(g1_cta && wg)) mbar_wait(bar(B_CF));
    wg_fence();
    wgmma64rs<0, 0, 128>(c, fa[0], dB1);
#pragma unroll
    for (int i = 1; i < 8; i++) wgmma64rs<1, 0, 128>(c, fa[i], dB1 + i * (2048 >> 4));
    wg_commit();
    float twc[8], tws[8], rho;
    uint32_t wo[4];
    {
      float w = after_here(0.0030679615757712823f, zr);
      float c, s, dc, ds;
      __sincosf(fmaf((float)pcol, 2.f * w, 0.7853981633974483f), &ds, &dc);
      rho = __fdividef(dc, ds);
      w *= (float)k1c;
      __sincosf(w * (float)t, &s, &c);
      c *= ds * 0.0013810679320049757f; s *= ds * 0.0013810679320049757f;
      __sincosf(w * 4.f, &ds, &dc);
#pragma unroll
      for (int n = 0; n < 8; n++) {
        twc[n] = c; tws[n] = s;
        if (n < 7) rot(c, s, dc, ds);
      }
      const int j0 = k1c + 64 * t, jn = SEQ - j0;
      wo[0] = sb + S3 + (j0 ^ (t << 3)) * 4;
      wo[1] = sb + S3 + 8192 + (jn ^ ((jn >> 3) & 24)) * 4;
      wo[2] = j0 ? wo[1] : wo[1] - 8192;
      wo[3] = __float_as_uint(rho) ^ __float_as_uint(c) ^ __float_as_uint(s);
      pin<4>(wo, zr);
    }
    wg_wait<0>();
    keep<32>(c);
    if ((tid & 127) == 0) mbar_arrive(bar(B_S1));
    uint32_t ap[16];
    float d[32];
    const uint32_t dG = dlo(sb + S2, 128);
#pragma unroll
    for (int nt = 0; nt < 8; nt++) {
      ap[2 * nt] = pack(c[4 * nt] * twc[nt] + c[4 * nt + 2] * tws[nt], c[4 * nt + 2] * twc[nt] - c[4 * nt] * tws[nt]);
      ap[2 * nt + 1] = pack(c[4 * nt + 1] * twc[nt] + c[4 * nt + 3] * tws[nt], c[4 * nt + 3] * twc[nt] - c[4 * nt + 1] * tws[nt]);
      if (nt & 1) {
        wg_fence();
        if (nt == 1) wgmma64rs<0, 0, 1024>(d, ap, dG); else wgmma64rs<1, 0, 1024>(d, ap + 2 * nt - 2, dG + (nt >> 1) * (256 >> 4));
      }
    }
    wg_commit();
    uint32_t wq[16];
    mbar_wait(bar(B_WQ));
#pragma unroll
    for (int i = 0; i < 8; i++) { wq[2 * i] = lds32(wo[0] + i * 1024); wq[2 * i + 1] = lds32(wo[i ? 1 : 2] - i * 1024); }
    wg_wait<0>();
    keep<32>(d);
#pragma unroll
    for (int nt = 0; nt < 8; nt++) {
      const float ar = d[4 * nt], ai = d[4 * nt + 1], br = d[4 * nt + 2], bi = d[4 * nt + 3];
      const float w1r = blo(wq[2 * nt]), w1i = bhi(wq[2 * nt]), w2r = blo(wq[2 * nt + 1]), w2i = bhi(wq[2 * nt + 1]);
      const float pr = fmaf(rho, ar, -bi), pi = fmaf(rho, ai, br), qr = fmaf(rho, br, -ai), qi = fmaf(rho, bi, ar);
      const float xr = pr * w1r - pi * w1i, xi = pr * w1i + pi * w1r, yr = qr * w2r + qi * w2i, yi = qi * w2r - qr * w2i;
      ap[2 * nt] = pack(fmaf(rho, xi, -yr), fmaf(rho, xr, yi));
      ap[2 * nt + 1] = pack(fmaf(rho, yi, -xr), fmaf(rho, yr, xi));
      if (nt & 1) {
        wg_fence();
        if (nt == 1) wgmma64rs<0, 0, 1024>(c, ap, dG); else wgmma64rs<1, 0, 1024>(c, ap + 2 * nt - 2, dG + (nt >> 1) * (256 >> 4));
      }
    }
    wg_commit();
#pragma unroll
    for (int i = 0; i < 8; i++) {
      const uint32_t cc = __byte_perm(fa[i][0], fa[i][2], 0x5410), ss = __byte_perm(fa[i][0], fa[i][2], 0x7632);
      fa[i][3] = __byte_perm(fa[i][1], fa[i][3], 0x7632);
      fa[i][0] = cc; fa[i][1] = ss ^ 0x80008000u; fa[i][2] = ss;
      keepu<4>(fa[i]);
    }
    mbar_wait(bar(B_S1));
    wg_wait<0>();
    keep<32>(c);
#pragma unroll
    for (int nt = 0; nt < 8; nt++) {
      ap[2 * nt] = pack(c[4 * nt] * twc[nt] + c[4 * nt + 1] * tws[nt], c[4 * nt + 2] * twc[nt] + c[4 * nt + 3] * tws[nt]);
      ap[2 * nt + 1] = pack(c[4 * nt + 1] * twc[nt] - c[4 * nt] * tws[nt], c[4 * nt + 3] * twc[nt] - c[4 * nt + 2] * tws[nt]);
    }
    {
      const int r = lane & 7, mi = lane >> 3;
      const uint32_t a = sb + S1 + warp * 2048 + (mi & 1) * 1024 + (mi >> 1) * 128 + (2 * (r & 3) + (r >> 2)) * 16;
#pragma unroll
      for (int i = 0; i < 4; i++) stsm4(a + i * 256, ap[4 * i], ap[4 * i + 1], ap[4 * i + 2], ap[4 * i + 3]);
    }
    fence_async_smem();
    nb_sync(NB_C, 256);
    wg_fence();
    wgmma64rs<0, 1, 128>(c, fa[0], dB1);
#pragma unroll
    for (int i = 1; i < 8; i++) wgmma64rs<1, 1, 128>(c, fa[i], dB1 + i * (2048 >> 4));
    wg_commit();
    unsigned char* zq = scr + G_Z + (k1c >> 2) * 8 * SLOT + (pcol & 127) * 128 + (((4 * t + (g & 3)) ^ ((pcol >> 1) & 15)) << 3);
    wg_wait<0>();
    keep<32>(c);
    if ((tid & 127) == 0) mbar_arrive(bar(B_S4));
    const bool zlate = g1_cta && (pcol & 127);
    if (!zlate) {
      if (pcol & 127) {
#pragma unroll
        for (int nt = 0; nt < 8; nt++) stg64(zq + nt * SLOT, pack(c[4 * nt], c[4 * nt + 2]), pack(-c[4 * nt + 1], c[4 * nt + 3]));
      } else {
#pragma unroll
        for (int nt = 0; nt < 8; nt++)
          stg32(zq + nt * SLOT + (pcol >> 5), pcol ? pack(-c[4 * nt + 1], c[4 * nt + 3]) : pack(c[4 * nt], c[4 * nt + 2]));
      }
      nb_arrive(NB_Z, 288);
    }
    if (main_cta) {
      float acc[64];
      gm.dA = dlo(sb + SLOT + wg * 8192, 8192); gm.dB = dlo(sb, 128);
      const int nz = ZK + (wg ? ZST : 0);
      gm.run<0, 16>(acc, 1, 0);
#pragma unroll
      for (int nt = 0; nt < 8; nt++)
        asm volatile("{\n.reg .pred p;\nsetp.ne.u32 p, %3, 0;\n@p st.global.v2.u32 [%0], {%1,%2};\n}" ::"l"(zq + nt * SLOT),
                     "r"(pack(c[4 * nt], c[4 * nt + 2])), "r"(pack(-c[4 * nt + 1], c[4 * nt + 3])), "r"((uint32_t)zlate) : "memory");
      if (zlate) nb_arrive(NB_Z, 288);
      gm.run<0, 16>(acc, nz - 1, 1);
      gm.drain();
      row_ifft<2>(rc, sb, scr, b, lane, warp >> 1, 2 * (warp & 1));
      gm.run<0, 16>(acc, 14 - TM - nz, 1);
      const int fo = (wt * 128 + warp * 16 + (lane >> 3)) * 1024 + (dt * 2 + rank) * 128 + (lane & 7) * 16;
      uint4 xv[4];
      auto load_x = [&]() {
#pragma unroll
      for (int i = 0; i < 4; i++)
        asm volatile("ld.global.nc.L1::no_allocate.v4.u32 {%0,%1,%2,%3}, [%4];" : "=r"(xv[i].x), "=r"(xv[i].y), "=r"(xv[i].z), "=r"(xv[i].w)
                     : "l"((const unsigned char*)P.x + fo + i * 4096) : "memory");
      };
      gm.tail<0, 16>(acc, wg, load_x, 0, sb + BIAS + 128 + (warp * 16 + g) * 2, peer + S1 + tid * 16, peer + MISC + 8 * B_XFULL2 + 16 * wg,
                     B_XFREE2);
      const uint32_t ga = sb + S1 + warp * 512;
      uint4 gv[4], sv[4];
      auto load_s = [&]() {
#pragma unroll
        for (int i = 0; i < 4; i++)
          asm volatile("ld.relaxed.gpu.global.v4.u32 {%0,%1,%2,%3}, [%4];" : "=r"(sv[i].x), "=r"(sv[i].y), "=r"(sv[i].z), "=r"(sv[i].w)
                       : "l"(scr + G_S + fo + i * 4096) : "memory");
      };
      bool have_s = false;
#pragma unroll
      for (int h = 0; h < 2; h++) {
        mbar_wait(bar(B_XFULL2 + h) + 16 * wg);
        if (!have_s && mbar_test(bar(B_FIN))) { load_s(); have_s = true; }
        const uint4 oa = lds128(sb + S1 + tid * 16 + h * 8192), ob = lds128(sb + S1 + tid * 16 + h * 8192 + 4096);
        const uint32_t o[8] = {oa.x, oa.y, oa.z, oa.w, ob.x, ob.y, ob.z, ob.w};
        uint32_t gs[8];
#pragma unroll
        for (int nt = 0; nt < 8; nt++) {
          const float y0 = fmaf(blo(o[nt]), 0.5f, acc[4 * nt + 2 * h]), y1 = fmaf(bhi(o[nt]), 0.5f, acc[4 * nt + 2 * h + 1]);
          gs[nt] = pack(fmaf(y0, tanh_fast(y0), y0), fmaf(y1, tanh_fast(y1), y1));
        }
        const uint32_t a = ga + h * 8192 + (lane & 4) * 1024 + (lane & 3) * 128 + (((lane >> 3) ^ (lane & 7)) << 4);
        __syncwarp();
        stsm4(a, gs[0], gs[1], gs[2], gs[3]);
        stsm4(a ^ 64, gs[4], gs[5], gs[6], gs[7]);
      }
      __syncwarp();
#pragma unroll
      for (int i = 0; i < 4; i++) gv[i] = lds128(ga + i * 4096 + (lane >> 3) * 128 + (((lane & 7) ^ (4 * (i & 1) + (lane >> 3))) << 4));
      if (!have_s) { mbar_wait(bar(B_FIN)); load_s(); }
#pragma unroll
      for (int i = 0; i < 4; i++)
        asm volatile("st.global.v4.u32 [%0], {%1,%2,%3,%4};" ::"l"((unsigned char*)P.out + fo + i * 4096), "r"(hfma2(sv[i].x, gv[i].x, xv[i].x)),
                     "r"(hfma2(sv[i].y, gv[i].y, xv[i].y)), "r"(hfma2(sv[i].z, gv[i].z, xv[i].z)), "r"(hfma2(sv[i].w, gv[i].w, xv[i].w)) : "memory");
    }
  } else if (threadIdx.x < 384) {
    asm volatile("setmaxnreg.dec.sync.aligned.u32 56;");
    ROLE_CTX
    if (b > 128) return;
    asm volatile("barrier.cluster.arrive.relaxed.aligned;" ::: "memory");
    const int hw = warp - 8, ht = tid - 256, kg = ht & 3;
    {
      const int pos = (ht >> 2) & 7, k1 = 2 * pos + (hw >> 1);
      float c, s, dc, ds;
      __sincosf((float)((k1 * 2 * kg + 4 * (hw & 1)) & 15) * 0.39269908169872414f, &s, &c);
      __sincosf((float)k1 * 0.39269908169872414f, &ds, &dc);
      const uint32_t e0 = pack(c, s), sg = (hw >> 1) ? 0x80008000u : 0u;
      rot(c, s, dc, ds);
      const uint32_t e1 = pack(c, s);
      asm volatile("st.shared.v4.u32 [%0], {%1,%2,%3,%4};" ::"r"(sb + RMAT + hw * 512 + kg * 128 + pos * 16), "r"(e0), "r"(e1),
                   "r"(e0 ^ sg), "r"(e1 ^ sg) : "memory");
      fence_async_smem();
    }
    asm volatile("barrier.cluster.wait.aligned;" ::: "memory");
    nb_arrive(NB_R, 384);
    if (main_cta && !g1_cta) {
      transpose_w(sb, scr, b, ht);
      nb_sync(NB_HLP, 128);
      if (hw == 3 && elect_one()) { signal(cnt(C_W), 1); mbar_arrive(bar(B_WDONE)); }
      __syncwarp();
    }
    if (g1_cta) mbar_wait(bar(B_STG));
    {
      const int k2 = ht >> 2;
      float c, s, dc, ds;
      __sincosf((float)((k2 * 8 * kg) & 31) * 0.19634954084936207f, &s, &c);
      __sincosf((float)k2 * 0.19634954084936207f, &ds, &dc);
#pragma unroll
      for (int q = 0; q < 2; q++) {
        uint32_t re[4], im[4];
#pragma unroll
        for (int i = 0; i < 4; i++) {
          re[i] = pack(c, s); im[i] = pack(-s, c);
          rot(c, s, dc, ds);
        }
        const uint32_t a = sb + S2 + ((k2 >> 2) * 8 + kg * 2 + q) * 128 + (k2 & 3) * 32;
        asm volatile("st.shared.v4.u32 [%0], {%1,%2,%3,%4};" ::"r"(a), "r"(re[0]), "r"(re[1]), "r"(re[2]), "r"(re[3]) : "memory");
        asm volatile("st.shared.v4.u32 [%0], {%1,%2,%3,%4};" ::"r"(a + 16), "r"(im[0]), "r"(im[1]), "r"(im[2]), "r"(im[3]) : "memory");
      }
      if (!main_cta) {
        mbar_wait(bar(B_WQ));
#pragma unroll 1
        for (int i = ht; i < 2 * 1025; i += 128) {
          const int j = i >> 1, jn = (SEQ - j) & (SEQ - 1);
          const uint32_t a0 = sb + S3 + (i & 1) * 8192, a = a0 + (j ^ ((j >> 3) & 24)) * 4, an = a0 + (jn ^ ((jn >> 3) & 24)) * 4;
          const uint32_t u = lds32(a), v = lds32(an), w = pack(0.5f * (blo(u) + blo(v)), 0.5f * (bhi(u) - bhi(v)));
          asm volatile("st.shared.u32 [%0], %1;" ::"r"(an), "r"(w ^ 0x80000000u) : "memory");
          asm volatile("st.shared.u32 [%0], %1;" ::"r"(a), "r"(w) : "memory");
        }
      }
      fence_async_smem();
      __syncwarp();
      if (lane == 0) mbar_arrive(bar(B_CF));
    }
  } else {
    asm volatile("setmaxnreg.dec.sync.aligned.u32 40;");
    ROLE_CTX
    if (b > 128) {
      const uint32_t t0 = clk();
      while (warp == 12 && clk() - t0 < PF_T) __nanosleep(200);
      if (BY_SM && warp == 12 && elect_one()) {
#pragma unroll 1
        for (int n = PF_0 * 8 + b - 129; n < PF_N * 8; n += 3)
          asm volatile("cp.async.bulk.prefetch.L2.global [%0], %1;" ::"l"((const unsigned char*)P.w2 +
                       ((n & 1) * 896 + (n >> 1) * 16) * (SEQ * 2)), "r"(65536) : "memory");
      }
      return;
    }
    if (warp == 12) {
      if (elect_one()) {
#pragma unroll
        for (int i = 0; i <= B_NONE; i++) mbar_init(bar(i), i < NS ? 1 : i < 2 * NS ? 2 : 0x7ffff);
        if (!g1_cta) {
#pragma unroll
          for (int i = B_WCH; i < B_STG; i++) mbar_init(bar(i), 1);
        }
        asm volatile("fence.mbarrier_init.release.cluster;" ::: "memory");
      }
      __syncwarp();
      asm volatile("barrier.cluster.arrive.relaxed.aligned;" ::: "memory");
      if (main_cta && elect_one()) {
        Ring r = {0, 1};
        if (g1_cta) {
          const int c0 = wt * 128 + rank * 64;
#pragma unroll 1
          for (int k = rank * 1024; k < rank * 1024 + 1024; k += 64) {
            const uint32_t d = sb + SLOT + r.s * STAGE, f = bar(B_FULL) + 8 * r.s;
            mbar_wait(f + 8 * NS, r.ph);
            tma2d(d, &mW1, c0, k, f);
            tma2d(d + 8192, &mW1, c0 ^ 64, k, f);
            r.next();
          }
        } else {
#pragma unroll 1
          for (int i = 0; i < 4; i++) {
            if (i >= 2) mbar_wait(bar(B_WCH + i - 2));
            const int go = ((b - 112) * 4 + i) * 16448;
            bulk_load(sb + i * WCH, (const unsigned char*)P.wr + go, 16448, bar(B_WCH + i));
            bulk_load(sb + i * WCH + 16448, (const unsigned char*)P.wi + go, 16448, bar(B_WCH + i));
            mbar_expect(bar(B_WCH + i), 32896);
          }
          mbar_wait(bar(B_WDONE));
        }
        if (g1_cta) mbar_wait(bar(B_FULL), 1);
#pragma unroll 1
        for (int k = rank * 896; k < rank * 896 + 896; k += 64) {
          const uint32_t d = sb + SLOT + r.s * STAGE, f = bar(B_FULL) + 8 * r.s;
          mbar_wait(f + 8 * NS, r.ph);
          tma2d(d, &mW2, wt * 128, k, f);
          tma2d(d + 8192, &mW2, wt * 128 + 64, k, f);
          r.next();
          if (k == rank * 896 + 768) r = {NS - 1, 0};
          if (k == rank * 896 + 64 * (GZ - 1)) mbar_wait(bar(B_Z));
        }
      }
    } else if (warp == 15) {
      if (elect_one()) {
#pragma unroll
        for (int i = B_STG; i < B_COUNT; i++) mbar_init(bar(i), i == B_STG ? 8 : i == B_CF ? 5 : i <= B_S1 ? 2 : 1);
        asm volatile("fence.mbarrier_init.release.cluster;" ::: "memory");
      }
      __syncwarp();
      asm volatile("barrier.cluster.arrive.relaxed.aligned;" ::: "memory");
      const void *ch = cnt(C_H + (pb >> 6)), *cu = cnt(C_U + dt * 2 + (wt >= 7)), *cz = cnt(C_Z), *cs = cnt(C_S + (wt & 15));
      const unsigned ih = 1u << (4 * ((pb >> 3) & 7)), iu = 1u << (2 * (wt >= 7 ? wt - 7 : wt) + rank);
      asm volatile("" : "+l"(ch), "+l"(cu), "+l"(cz), "+l"(cs));
      if (main_cta) {
        nb_sync(NB_H, 288);
        if (elect_one()) signal(ch, ih);
        __syncwarp();
      }
      if (g1_cta) {
        nb_sync(NB_U, 288);
        if (elect_one()) signal(cu, iu);
        __syncwarp();
      }
      nb_sync(NB_Z, 288);
      if (elect_one()) signal(cz, main_cta ? 1 : 128);
      __syncwarp();
      if (main_cta) {
        nb_sync(NB_S, 288);
        if (elect_one()) signal(cs, 1);
      }
    } else {
      asm volatile("barrier.cluster.arrive.relaxed.aligned;" ::: "memory");
      const unsigned ep = ld_relaxed(cnt(C_EPOCH));
      asm volatile("barrier.cluster.wait.aligned;" ::: "memory");
      if (warp == 13) {
        if (main_cta && elect_one()) {
          Ring r = {0, 1};
          unsigned seen = 0;
          if (g1_cta) {
            const unsigned char* src = scr + G_H + (dt * 32 + rank * 16) * SLOT;
#pragma unroll 1
            for (int i = 0; i < 16; i++) {
              const uint32_t d = sb + r.s * STAGE, f = bar(B_FULL) + 8 * r.s;
              mbar_wait(f + 8 * NS, r.ph);
              poll(cnt(C_H + rank), ep * 0x88888888u, 8u << (2 * (i & 14)), seen);
              bulk_load(d, src, SLOT, f);
              mbar_expect(f, STAGE);
              src += SLOT;
              r.next();
            }
          } else {
            mbar_wait(bar(B_WDONE));
          }
          seen = 0;
          const unsigned char* src = scr + G_U + (dt * 28 + rank * 14) * SLOT + rank * 8192;
          const int oth = rank ? -8192 : 8192;
#pragma unroll 1
          for (int i = 0; i < 14; i++) {
            const uint32_t d = sb + r.s * STAGE, f = bar(B_FULL) + 8 * r.s;
            mbar_wait(f + 8 * NS, r.ph);
            poll(cnt(C_U + dt * 2 + rank), ep * 0x3fffu, 1u << i, seen);
            bulk_load(d, src, 8192, f);
            bulk_load(d + 8192, src + oth, 8192, f);
            mbar_expect(f, STAGE);
            src += SLOT;
            r.next();
            if (i == 12) r = {NS - 1, 0};
            if (i == GZ - 1) mbar_wait(bar(B_Z));
          }
        }
      } else if (elect_one()) {
        const uint32_t peer = mapa(sb, rank ^ 1);
#pragma unroll
        for (int i = 0; i < 8; i++) mbar_expect(bar(B_XFULL1 + i), SLOT / 4);
        if (main_cta) {
          bulk_load(sb + BIAS, P.b1 + (g1_cta ? wt : 0) * 128 + rank * 64, 128, bar(B_XFREE1));
          bulk_load(sb + BIAS + 128, P.b2 + wt * 128, 256, bar(B_XFREE1));
          mbar_expect(bar(B_XFREE1), 388);
          prefetch_map(&mX1);
          mbar_wait(bar(B_STG));
          if (g1_cta) mbar_wait(bar(B_FULL + 3));
          bulk_store(scr + G_X1 + 128 * SLOT + pb * 128, sb + XTRA, 128);
          const uint32_t t1 = clk();
#pragma unroll 1
          for (int n = 0; n < 4; n++) {
            wait_until(t1, n * X1_DT);
            tma2d_store(&mX1, pb * 64, 32 * n, sb + S0 + n * 4096);
          }
          bulk_commit();
          bulk_wait_all();
          asm volatile("st.async.weak.shared::cluster.mbarrier::complete_tx::bytes.b32 [%0], %1, [%2];" ::"r"(peer + WHO), "r"(b),
                       "r"(peer + MISC + 8 * B_XFREE1) : "memory");
          mbar_arrive_cluster(peer + MISC + 8 * B_XFREE1);
          signal(cnt(C_X), 1);
          prefetch_map(&mW2);
        }
        poll(cnt(C_X), ep * 128, 128);
        bulk_load(sb + S1, scr + G_X1 + b * SLOT, SLOT, bar(B_CF));
        mbar_expect(bar(B_CF), SLOT);
        const int pcol = b == 0 ? 128 : (b & 0x70) | ((b & 7) << 1) | ((b >> 3) & 1);
        const uint32_t wb = bar(B_WQ);
        poll(cnt(C_W), ep * 16, 16);
        if (g1_cta) mbar_wait(bar(B_XFULL1));
        bulk_load(sb + S3, scr + G_WT + pcol * 8192, 8192, wb);
        bulk_load(sb + S3 + 8192, scr + G_WT + (256 - pcol) * 8192, 8192, wb);
        mbar_expect(wb, SLOT);
        if (main_cta) {
          mbar_wait(bar(B_XFREE1));
          asm volatile("{\n.reg .pred p;\nsetp.ne.u32 p, %0, %1;\n@p trap;\n}" ::"r"(lds32(sb + WHO)), "r"(b ^ 1));
          mbar_wait(bar(B_S4));
          mbar_arrive_cluster(peer + MISC + 8 * B_XFREE2);
          poll(cnt(C_Z), ep * 256, 256);
          bulk_load(sb + S0, scr + G_Z + b * SLOT, SLOT, bar(B_Z));
          mbar_expect(bar(B_Z), SLOT);
          if (b == 0) asm volatile("st.relaxed.gpu.global.u32 [%0], %1;" ::"l"(cnt(C_EPOCH)), "r"(ep + 1) : "memory");
          poll(cnt(C_S + wt), ep * 8, 8);
          mbar_arrive(bar(B_FIN));
        }
      }
    }
  }
}

typedef CUresult (*EncodeFn)(CUtensorMap*, CUtensorMapDataType, cuuint32_t, void*, const cuuint64_t*, const cuuint64_t*,
                             const cuuint32_t*, const cuuint32_t*, CUtensorMapInterleave, CUtensorMapSwizzle,
                             CUtensorMapL2promotion, CUtensorMapFloatOOBfill);

CUtensorMap make_map(EncodeFn enc, const void* p, int inner, int outer, int box_rows) {
  CUtensorMap m;
  cuuint64_t dims[2] = {(cuuint64_t)inner, (cuuint64_t)outer};
  cuuint64_t st[1] = {(cuuint64_t)inner * 2};
  cuuint32_t box[2] = {64u, (cuuint32_t)box_rows};
  cuuint32_t es[2] = {1, 1};
  enc(&m, CU_TENSOR_MAP_DATA_TYPE_BFLOAT16, 2, const_cast<void*>(p), dims, st, box, es, CU_TENSOR_MAP_INTERLEAVE_NONE,
      CU_TENSOR_MAP_SWIZZLE_128B, CU_TENSOR_MAP_L2_PROMOTION_L2_128B, CU_TENSOR_MAP_FLOAT_OOB_FILL_NONE);
  return m;
}

__global__ void probe_kernel() {}
bool place_tpcs(int* slot) {
  int dev = 0, sms = 0, fit[17] = {};
  cudaGetDevice(&dev);
  cudaDeviceGetAttribute(&sms, cudaDevAttrMultiProcessorCount, dev);
  if (sms != NCTA) return false;
  cudaFuncSetAttribute(probe_kernel, cudaFuncAttributeMaxDynamicSharedMemorySize, SMEM_BYTES);
  cudaFuncSetAttribute(probe_kernel, cudaFuncAttributeNonPortableClusterSizeAllowed, 1);
  for (int c = 2; c <= 16; c++) {
    cudaLaunchConfig_t cfg = {};
    cudaLaunchAttribute at;
    at.id = cudaLaunchAttributeClusterDimension;
    at.val.clusterDim.x = c; at.val.clusterDim.y = 1; at.val.clusterDim.z = 1;
    cfg.gridDim = dim3(c); cfg.blockDim = dim3(32); cfg.dynamicSmemBytes = SMEM_BYTES; cfg.attrs = &at; cfg.numAttrs = 1;
    if (cudaOccupancyMaxActiveClusters(&fit[c], probe_kernel, &cfg) != cudaSuccess) {
      (void)cudaGetLastError();
      return false;
    }
  }
  int num[10] = {}, size[66], ng = 0;
  num[9] = fit[9] - fit[10];
  for (int t = 8; t >= 1; t--) {
    num[t] = fit[2 * t];
    for (int u = t + 1; u <= 9; u++) num[t] -= num[u] * (u / t);
  }
  for (int t = 1; t <= 9; t++)
    if (num[t] < 0 || num[t] > 66) return false;
  if (fit[2] != 66) return false;
  for (int t = 2; t <= 9; t++)
    for (int i = 0; i < num[t]; i++) size[ng++] = t;
  int first[67], tpc = 0;
  first[ng] = 0;
  for (int g = ng - 1; g >= 0; g--) first[g] = first[g + 1] + (size[g] < 8 ? size[g] : 8);
  int extra = first[0] + num[1];
  for (int r = 0; r < 9; r++)
    for (int g = 0; g < ng; g++)
      if (size[g] > r) slot[tpc++] = r < 8 ? first[g + 1] + r : extra++;
  for (int i = first[0]; tpc < 66;) slot[tpc++] = i++;
  return true;
}

}

extern "C" void kernel_launch(void* const* d_in, const int* in_sizes, int n_in, void* d_out, int out_size) {
  (void)in_sizes; (void)n_in; (void)out_size;
  static EncodeFn enc = nullptr;
  static void* scr = nullptr;
  static bool by_sm = false;
  static int slot[66];
  if (!enc) {
    void* fn = nullptr;
    cudaDriverEntryPointQueryResult q;
    cudaGetDriverEntryPoint("cuTensorMapEncodeTiled", &fn, cudaEnableDefault, &q);
    enc = (EncodeFn)fn;
    cudaGetSymbolAddress(&scr, g_scr);
    cudaFuncSetAttribute(fused_kernel<true>, cudaFuncAttributeMaxDynamicSharedMemorySize, SMEM_BYTES);
    cudaFuncSetAttribute(fused_kernel<false>, cudaFuncAttributeMaxDynamicSharedMemorySize, SMEM_BYTES);
    by_sm = place_tpcs(slot);
  }
  Params P;
  P.x = (const __nv_bfloat16*)d_in[0];
  P.wr = (const __nv_bfloat16*)d_in[1];
  P.wi = (const __nv_bfloat16*)d_in[2];
  P.b1 = (const __nv_bfloat16*)d_in[5];
  P.w2 = (const __nv_bfloat16*)d_in[6];
  P.b2 = (const __nv_bfloat16*)d_in[7];
  P.scr = (unsigned char*)scr;
  P.out = d_out;
  P.zero = 0;
  const int order[14] = {0, 8, 1, 9, 2, 10, 3, 11, 4, 12, 5, 13, 6, 7};
  for (int i = 0; i < NCTA; i++) {
    const int b = by_sm ? 2 * slot[i >> 1] + (i & 1) : i, idx = (b & 15) * 7 + (b >> 4);
    const int pb = b < 112 ? order[idx >> 3] * 8 + (idx & 7) : b & 127;
    P.tab[i] = b | ((pb & 0x78) << 14) | ((pb & 7) << 12) | ((X_ST * ((pb >> 3) & 7)) << 21);
  }
  const CUtensorMap mW1 = make_map(enc, d_in[4], FF, SEQ, 64);
  const CUtensorMap mW2 = make_map(enc, d_in[6], SEQ, FF, 64);
  const CUtensorMap mX1 = make_map(enc, P.scr + G_X1, 8192, 129, 32);
  if (by_sm) fused_kernel<true><<<NCTA, NTHR, SMEM_BYTES, cudaStreamPerThread>>>(P, mW1, mW2, mX1);
  else fused_kernel<false><<<NCTA - 2, NTHR, SMEM_BYTES, cudaStreamPerThread>>>(P, mW1, mW2, mX1);
}
```

```cpp
#include <cuda_runtime.h>
#include <cuda_bf16.h>
#include <cuda.h>
#include <stdint.h>

constexpr int X1_DT = 500;
constexpr int TM = 3;
constexpr int ZK = 8;
constexpr int ZST = 2;
constexpr int GZ = 11;
constexpr int H_LATE = 2;
constexpr int X_ST = 80;

namespace {

constexpr int SEQ = 2048, DM = 512, FF = 1792, DF = 257;
constexpr int NCTA = 132;
constexpr int NTHR = 512;
constexpr int SLOT = 16384;
constexpr int NS = 6, STAGE = 2 * SLOT;
constexpr int S2 = 10 * SLOT, S3 = 11 * SLOT, S0 = 12 * SLOT, S1 = 13 * SLOT;
constexpr int WCH = 33024;
constexpr int XTRA = 14 * SLOT;
constexpr int MISC = 14 * SLOT + 128;
constexpr int BIAS = 14 * SLOT + 512;
constexpr int WHO = 14 * SLOT + 1008;
constexpr int RMAT = 14 * SLOT + 1024;
constexpr int SMEM_BYTES = RMAT + 2048;

constexpr int B_FULL = 0, B_EMPTY = NS, B_S4 = B_EMPTY + 5, B_NONE = 2 * NS, B_WCH = 13, B_WDONE = 17,
              B_STG = 18, B_CF = 19, B_XFREE1 = 20, B_S1 = 21, B_XFREE2 = 22, B_Z = 23, B_FIN = 24,
              B_WQ = 25, B_XFULL1 = 26, B_XFULL2 = 30, B_COUNT = 34;
constexpr int NB_H = 1, NB_U = 2, NB_Z = 3, NB_C = 4, NB_HLP = 5, NB_R = 6, NB_S = 7, NB_T = 8;

constexpr int G_H = 0;
constexpr int G_U = G_H + 128 * SLOT;
constexpr int G_Z = G_U + 112 * SLOT;
constexpr int G_S = G_Z + 128 * SLOT;
constexpr int G_X1 = G_S + 128 * SLOT;
constexpr int G_WT = G_X1 + 129 * SLOT;
constexpr int G_CNT = G_WT + DF * SEQ * 4;
constexpr int C_H = 0, C_X = 2, C_W = 3, C_Z = 4, C_EPOCH = 5, C_U = 6, C_S = 14, C_COUNT = 30;
__device__ __align__(1024) unsigned char g_scr[G_CNT + C_COUNT * 128];

__device__ __forceinline__ void mbar_init(uint32_t b, int c) {
  asm volatile("mbarrier.init.shared::cta.b64 [%0], %1;" ::"r"(b), "r"(c) : "memory");
}
__device__ __forceinline__ void mbar_expect(uint32_t b, int bytes) {
  asm volatile("mbarrier.arrive.expect_tx.shared::cta.b64 _, [%0], %1;" ::"r"(b), "r"(bytes) : "memory");
}
__device__ __forceinline__ void mbar_arrive(uint32_t b) {
  asm volatile("mbarrier.arrive.shared::cta.b64 _, [%0];" ::"r"(b) : "memory");
}
__device__ __forceinline__ void mbar_arrive_cluster(uint32_t remote) {
  asm volatile("mbarrier.arrive.shared::cluster.b64 _, [%0];" ::"r"(remote) : "memory");
}
__device__ __forceinline__ void mbar_wait(uint32_t b, int ph = 0) {
  asm volatile("{\n.reg .pred p;\n.reg .u32 n;\n"
               "mbarrier.try_wait.parity.shared::cta.b64 p, [%0], %1;\n@p bra WD;\n"
               "mov.u32 n, 0;\nWL:\n"
               "mbarrier.try_wait.parity.shared::cta.b64 p, [%0], %1, 4000;\n@p bra WD;\n"
               "add.u32 n, n, 1;\nsetp.lt.u32 p, n, 0x20000;\n@p bra WL;\ntrap;\nWD:\n}" ::"r"(b), "r"(ph) : "memory");
}
__device__ __forceinline__ bool mbar_test(uint32_t b) {
  uint32_t ok;
  asm volatile("{\n.reg .pred p;\nmbarrier.test_wait.parity.shared::cta.b64 p, [%1], 0;\nselp.u32 %0, 1, 0, p;\n}" : "=r"(ok) : "r"(b) : "memory");
  return ok;
}
__device__ __forceinline__ bool elect_one() {
  uint32_t p;
  asm volatile("{\n.reg .pred e;\nelect.sync _|e, 0xffffffff;\nselp.u32 %0, 1, 0, e;\n}" : "=r"(p));
  return p;
}
__device__ __forceinline__ uint32_t mapa(uint32_t a, uint32_t cta) {
  uint32_t r;
  asm("mapa.shared::cluster.u32 %0, %1, %2;" : "=r"(r) : "r"(a), "r"(cta));
  return r;
}
__device__ __forceinline__ void tma2d(uint32_t dst, const CUtensorMap* m, int c0, int c1, uint32_t bar) {
  asm volatile("cp.async.bulk.tensor.2d.shared::cluster.global.mbarrier::complete_tx::bytes [%0], [%1, {%3, %4}], [%2];"
               ::"r"(dst), "l"(m), "r"(bar), "r"(c0), "r"(c1) : "memory");
}
__device__ __forceinline__ void tma2d_store(const CUtensorMap* m, int c0, int c1, uint32_t src) {
  asm volatile("cp.async.bulk.tensor.2d.global.shared::cta.bulk_group [%0, {%2, %3}], [%1];"
               ::"l"(m), "r"(src), "r"(c0), "r"(c1) : "memory");
}
__device__ __forceinline__ void bulk_load(uint32_t dst, const void* src, int bytes, uint32_t bar) {
  asm volatile("cp.async.bulk.shared::cluster.global.mbarrier::complete_tx::bytes [%0], [%1], %2, [%3];"
               ::"r"(dst), "l"(src), "r"(bytes), "r"(bar) : "memory");
}
__device__ __forceinline__ void bulk_store(void* dst, uint32_t src, int bytes) {
  asm volatile("cp.async.bulk.global.shared::cta.bulk_group [%0], [%1], %2;" ::"l"(dst), "r"(src), "r"(bytes) : "memory");
}
__device__ __forceinline__ void bulk_commit() { asm volatile("cp.async.bulk.commit_group;" ::: "memory"); }
__device__ __forceinline__ void bulk_wait_all() { asm volatile("cp.async.bulk.wait_group 0;" ::: "memory"); }
__device__ __forceinline__ void fence_async_smem() { asm volatile("fence.proxy.async.shared::cta;" ::: "memory"); }
__device__ __forceinline__ void prefetch_map(const CUtensorMap* m) {
  asm volatile("prefetch.tensormap [%0];" ::"l"(m) : "memory");
}
__device__ __forceinline__ void nb_sync(int id, int n) { asm volatile("bar.sync %0, %1;" ::"r"(id), "r"(n) : "memory"); }
__device__ __forceinline__ void nb_arrive(int id, int n) { asm volatile("bar.arrive %0, %1;" ::"r"(id), "r"(n) : "memory"); }
__device__ __forceinline__ void signal(const void* cnt, unsigned inc) {
  asm volatile("fence.proxy.async;\nred.relaxed.gpu.global.add.u32 [%0], %1;" ::"l"(cnt), "r"(inc) : "memory");
}
__device__ __forceinline__ unsigned ld_relaxed(const void* p) {
  unsigned v;
  asm volatile("ld.relaxed.gpu.global.u32 %0, [%1];" : "=r"(v) : "l"(p) : "memory");
  return v;
}
__device__ __forceinline__ void poll(const void* cnt, unsigned base, unsigned mask, unsigned& seen) {
  asm volatile("{\n.reg .pred p;\n.reg .u32 n, v;\nand.b32 v, %0, %3;\nsetp.ne.u32 p, v, 0;\n@p bra PD;\nmov.u32 n, 0;\nPL:\n"
               "ld.acquire.gpu.global.u32 v, [%1];\nsub.u32 %0, v, %2;\nand.b32 v, %0, %3;\nsetp.ne.u32 p, v, 0;\n@p bra PD;\n"
               "add.u32 n, n, 1;\nsetp.lt.u32 p, n, 0x200000;\n@p bra PL;\ntrap;\nPD:\n}"
               : "+r"(seen) : "l"(cnt), "r"(base), "r"(mask) : "memory");
}
__device__ __forceinline__ void poll(const void* cnt, unsigned base, unsigned mask) {
  unsigned seen = 0;
  poll(cnt, base, mask, seen);
}
__device__ __forceinline__ void stg32(void* p, uint32_t a) { asm volatile("st.global.u32 [%0], %1;" ::"l"(p), "r"(a) : "memory"); }
__device__ __forceinline__ void stg64(void* p, uint32_t a, uint32_t b) {
  asm volatile("st.global.v2.u32 [%0], {%1,%2};" ::"l"(p), "r"(a), "r"(b) : "memory");
}
__device__ __forceinline__ uint32_t pack(float lo, float hi) {
  uint32_t r;
  asm("cvt.rn.bf16x2.f32 %0, %1, %2;" : "=r"(r) : "f"(hi), "f"(lo));
  return r;
}
__device__ __forceinline__ float blo(uint32_t v) { return __uint_as_float(v << 16); }
__device__ __forceinline__ float bhi(uint32_t v) { return __uint_as_float(v & 0xffff0000u); }
__device__ __forceinline__ uint32_t hfma2(uint32_t a, uint32_t b, uint32_t c) {
  uint32_t r;
  asm("fma.rn.bf16x2 %0, %1, %2, %3;" : "=r"(r) : "r"(a), "r"(b), "r"(c));
  return r;
}
__device__ __forceinline__ float rsqrt_fast(float x) {
  float r;
  asm("rsqrt.approx.f32 %0, %1;" : "=f"(r) : "f"(x));
  return r;
}
__device__ __forceinline__ float tanh_fast(float x) {
  float r;
  asm("tanh.approx.f32 %0, %1;" : "=f"(r) : "f"(x));
  return r;
}
__device__ __forceinline__ uint32_t movm(uint32_t a) {
  uint32_t d;
  asm("movmatrix.sync.aligned.m8n8.trans.b16 %0, %1;" : "=r"(d) : "r"(a));
  return d;
}
__device__ __forceinline__ void stsm4(uint32_t a, uint32_t r0, uint32_t r1, uint32_t r2, uint32_t r3) {
  asm volatile("stmatrix.sync.aligned.m8n8.x4.shared.b16 [%0], {%1,%2,%3,%4};" ::"r"(a), "r"(r0), "r"(r1), "r"(r2), "r"(r3) : "memory");
}
__device__ __forceinline__ void ldsm4t(uint32_t a, uint32_t* r) {
  asm volatile("ldmatrix.sync.aligned.m8n8.x4.trans.shared.b16 {%0,%1,%2,%3}, [%4];"
               : "=r"(r[0]), "=r"(r[1]), "=r"(r[2]), "=r"(r[3]) : "r"(a) : "memory");
}
__device__ __forceinline__ void st_async4(uint32_t a, uint32_t r0, uint32_t r1, uint32_t r2, uint32_t r3, uint32_t bar) {
  asm volatile("st.async.weak.shared::cluster.mbarrier::complete_tx::bytes.v4.b32 [%0], {%1,%2,%3,%4}, [%5];"
               ::"r"(a), "r"(r0), "r"(r1), "r"(r2), "r"(r3), "r"(bar) : "memory");
}
__device__ __forceinline__ uint4 lds128(uint32_t a) {
  uint4 v;
  asm volatile("ld.shared.v4.u32 {%0,%1,%2,%3}, [%4];" : "=r"(v.x), "=r"(v.y), "=r"(v.z), "=r"(v.w) : "r"(a) : "memory");
  return v;
}
__device__ __forceinline__ uint32_t lds32(uint32_t a) {
  uint32_t v;
  asm volatile("ld.shared.u32 %0, [%1];" : "=r"(v) : "r"(a) : "memory");
  return v;
}
__device__ __forceinline__ uint32_t clk() {
  uint32_t c;
  asm volatile("mov.u32 %0, %%clock;" : "=r"(c));
  return c;
}
__device__ __forceinline__ void wait_until(uint32_t t0, int dt) {
  while ((int)(clk() - t0) < dt) {}
}
__device__ __forceinline__ uint32_t dlo(uint32_t addr, uint32_t lbo) { return ((addr & 0x3FFFF) >> 4) | ((lbo >> 4) << 16); }
__host__ __device__ constexpr uint32_t dhi(uint32_t sbo, uint32_t sw) { return (sbo >> 4) | (sw << 30); }
__device__ __forceinline__ void wg_fence() { asm volatile("wgmma.fence.sync.aligned;" ::: "memory"); }
__device__ __forceinline__ void wg_commit() { asm volatile("wgmma.commit_group.sync.aligned;" ::: "memory"); }
template <int N> __device__ __forceinline__ void wg_wait() { asm volatile("wgmma.wait_group.sync.aligned %0;" ::"n"(N) : "memory"); }
template <int N> __device__ __forceinline__ void keep(float* d) {
#pragma unroll
  for (int i = 0; i < N; i++) asm volatile("" : "+f"(d[i])::"memory");
}
template <int N> __device__ __forceinline__ void renew(float* d) {
#pragma unroll
  for (int i = 0; i < N; i++) asm volatile("mov.b32 %0, %1;" : "=f"(d[i]) : "f"(d[i]) : "memory");
}
template <int N> __device__ __forceinline__ void pin(const void* v, uint32_t zero) {
  const uint32_t* d = (const uint32_t*)v;
  uint32_t x = 0;
#pragma unroll
  for (int i = 0; i < N; i++) x ^= d[i];
  asm volatile("{\n.reg .pred p;\nsetp.ne.u32 p, %1, 0;\n@p st.shared.b32 [%1], %0;\n}" ::"r"(x), "r"(zero) : "memory");
}
__device__ __forceinline__ float after_here(float v, uint32_t zero) {
  uint32_t r = __float_as_uint(v);
  asm volatile("{\n.reg .pred p;\n.reg .u32 n;\nmov.u32 n, %1;\nSF:\nadd.u32 %0, %0, n;\nsetp.ne.u32 p, n, 0;\nshr.u32 n, n, 1;\n@p bra SF;\n}"
               : "+r"(r) : "r"(zero) : "memory");
  return __uint_as_float(r);
}
template <int N> __device__ __forceinline__ void keepu(uint32_t* d) {
#pragma unroll
  for (int i = 0; i < N; i++) asm volatile("" : "+r"(d[i])::"memory");
}
#define R8(c, o) c(d[o]), c(d[o + 1]), c(d[o + 2]), c(d[o + 3]), c(d[o + 4]), c(d[o + 5]), c(d[o + 6]), c(d[o + 7])
#define D32 "%0,%1,%2,%3,%4,%5,%6,%7,%8,%9,%10,%11,%12,%13,%14,%15,%16,%17,%18,%19,%20,%21,%22,%23,%24,%25,%26,%27,%28,%29,%30,%31"
#define D64 D32 ",%32,%33,%34,%35,%36,%37,%38,%39,%40,%41,%42,%43,%44,%45,%46,%47,%48,%49,%50,%51,%52,%53,%54,%55,%56,%57,%58,%59,%60,%61,%62,%63"
template <int TB> __device__ __forceinline__ void wgmma128(float* d, uint32_t a, uint32_t b, int accum) {
  asm volatile("{\n.reg .b64 da, db;\n.reg .pred p;\nsetp.ne.b32 p, %69, 0;\nmov.b64 da, {%64, %67};\nmov.b64 db, {%65, %68};\n"
               "wgmma.mma_async.sync.aligned.m64n128k16.f32.bf16.bf16 {" D64 "}, da, db, p, 1, 1, 1, %66;\n}"
               : R8("+f", 0), R8("+f", 8), R8("+f", 16), R8("+f", 24), R8("+f", 32), R8("+f", 40), R8("+f", 48), R8("+f", 56)
               : "r"(a), "r"(b), "n"(TB), "n"(dhi(1024, 1)), "n"(dhi(1024, TB)), "r"(accum));
}
template <int ACC, int TB, int SBO, int SW = 0>
__device__ __forceinline__ void wgmma64rs(float* d, const uint32_t* a, uint32_t b) {
  asm volatile("{\n.reg .b64 db;\nmov.b64 db, {%36, %39};\n"
               "wgmma.mma_async.sync.aligned.m64n64k16.f32.bf16.bf16 {" D32 "}, {%32,%33,%34,%35}, db, %37, 1, 1, %38;\n}"
               : R8("+f", 0), R8("+f", 8), R8("+f", 16), R8("+f", 24)
               : "r"(a[0]), "r"(a[1]), "r"(a[2]), "r"(a[3]), "r"(b), "n"(ACC), "n"(TB), "n"(dhi(SBO, SW)));
}
template <int ACC, int TB, int SBO>
__device__ __forceinline__ void wgmma32rs(float* d, const uint32_t* a, uint32_t b) {
  asm volatile("{\n.reg .b64 db;\nmov.b64 db, {%20, %23};\n"
               "wgmma.mma_async.sync.aligned.m64n32k16.f32.bf16.bf16 {%0,%1,%2,%3,%4,%5,%6,%7,%8,%9,%10,%11,%12,%13,%14,%15}, "
               "{%16,%17,%18,%19}, db, %21, 1, 1, %22;\n}"
               : R8("+f", 0), R8("+f", 8)
               : "r"(a[0]), "r"(a[1]), "r"(a[2]), "r"(a[3]), "r"(b), "n"(ACC), "n"(TB), "n"(dhi(SBO, 0)));
}

struct RowConst { float c[2][4], s[2][4]; };
__device__ __forceinline__ void rot(float& c, float& s, float dc, float ds) {
  const float n = c * dc - s * ds;
  s = s * dc + c * ds;
  c = n;
}
__device__ __forceinline__ void row_const(RowConst& r, int lane) {
  const int g = lane >> 2, t = lane & 3;
#pragma unroll
  for (int h = 0; h < 2; h++) {
    const float w = (float)(2 * g + h) * 0.02454369260617026f;
    float c, s, dc, ds;
    __sincosf(w * (float)(4 * t), &s, &c);
    __sincosf(w, &ds, &dc);
#pragma unroll
    for (int k = 0; k < 4; k++) {
      r.c[h][2 * (k & 1) + (k >> 1)] = c; r.s[h][2 * (k & 1) + (k >> 1)] = s;
      if (k < 3) rot(c, s, dc, ds);
    }
  }
}
template <int NR> __device__ __forceinline__ void row_step1(uint32_t sb, const uint32_t (*a)[8], float (*z)[16]) {
  const uint32_t d = dlo(sb + RMAT, 128);
#pragma unroll
  for (int r = 0; r < NR; r++) {
    wgmma32rs<0, 0, 512>(z[r], a[r], d);
    wgmma32rs<1, 0, 512>(z[r], a[r] + 4, d + (256 >> 4));
  }
  wg_commit();
}
template <int NR> __device__ __forceinline__ void row_twiddle(const RowConst& rc, uint32_t (*a)[8], float (*z)[16]) {
#pragma unroll
  for (int r = 0; r < NR; r++) {
    keep<16>(z[r]);
#pragma unroll
    for (int h = 0; h < 2; h++)
#pragma unroll
      for (int u = 0; u < 2; u++) {
        const float r0 = z[r][8 * u + 2 * h], r1 = z[r][8 * u + 2 * h + 1], i0 = z[r][8 * u + 4 + 2 * h], i1 = z[r][8 * u + 5 + 2 * h];
        const float c0 = rc.c[h][2 * u], s0 = rc.s[h][2 * u], c1 = rc.c[h][2 * u + 1], s1 = rc.s[h][2 * u + 1];
        a[r][4 * h + u] = movm(pack(i0 * c0 - r0 * s0, i1 * c1 - r1 * s1));
        a[r][4 * h + 2 + u] = movm(pack(r0 * c0 + i0 * s0, r1 * c1 + i1 * s1));
      }
    keepu<8>(a[r]);
  }
}
template <int NR> __device__ __forceinline__ void row_step2(uint32_t sb, const uint32_t (*a)[8], float (*z)[16]) {
  const uint32_t d = dlo(sb + RMAT, 512);
#pragma unroll
  for (int r = 0; r < NR; r++) {
    wgmma32rs<0, 1, 128>(z[r], a[r], d);
    wgmma32rs<1, 1, 128>(z[r], a[r] + 4, d + (1024 >> 4));
  }
  wg_commit();
}

struct Params {
  const __nv_bfloat16* x;
  unsigned char* scr;
  void* out;
  uint32_t zero;
  uint32_t tab[132];
  const __nv_bfloat16 *wr, *wi, *w2, *b1, *b2;
};

template <int NR>
__device__ __forceinline__ void row_ifft(const RowConst& rc, uint32_t sb, unsigned char* scr, int b, int lane, int q, int i0) {
  const int g = lane >> 2, t = lane & 3;
  const int col = t >> 1;
  uint32_t za[2], A[NR][8];
#pragma unroll
  for (int h = 0; h < 2; h++) {
    const int kl = 16 * (t & 1) + 2 * g + h, p = col ? 128 - kl : kl;
    za[h] = sb + S0 + p * 128 + (((4 * q + i0) ^ ((p >> 1) & 15)) << 3) + col * 4;
  }
  const int stp = col ? -4096 : 4096;
  float z[NR][16];
  mbar_wait(sb + MISC + 8 * B_Z);
#pragma unroll
  for (int r = 0; r < NR; r++)
#pragma unroll
    for (int j = 0; j < 8; j++)
      A[r][j] = lds32((j ? za[j & 1] + (j >> 1) * stp : lane == 2 ? za[0] - SLOT : za[0]) ^ (r << 3));
  wg_fence();
  row_step1<NR>(sb, A, z);
  wg_wait<0>();
  row_twiddle<NR>(rc, A, z);
  wg_fence();
  row_step2<NR>(sb, A, z);
  unsigned char* sp = scr + G_S + ((b >> 3) * 128 + 32 * i0 + 4 * (b & 7) + q) * 1024 + col * 512 + (t & 1) * 64 + g * 8;
  wg_wait<0>();
#pragma unroll
  for (int r = 0; r < NR; r++) {
    keep<16>(z[r]);
#pragma unroll
    for (int j = 0; j < 4; j++)
      stg64(sp + r * 32768 + j * 128, pack(z[r][4 * j], z[r][4 * j + 1]), pack(z[r][4 * j + 2], z[r][4 * j + 3]));
  }
  nb_arrive(NB_S, 288);
}

__device__ __forceinline__ void transpose_w(uint32_t sb, unsigned char* scr, int b, int ht) {
#pragma unroll 1
  for (int ch = 0; ch < 4; ch++) {
    unsigned char* wp = scr + G_WT + (ht >> 3) * 8192 + (b - 112) * 512 + ch * 128 +
                        (((ht & 7) * 16) ^ (((b & 1) * 2 + (ch >> 1)) << 5));
    uint32_t a = sb + ch * WCH + (4 * (ht & 7) * DF + (ht >> 3)) * 2;
    mbar_wait(sb + MISC + 8 * (B_WCH + ch));
#pragma unroll 1
    for (int n0 = 0; n0 < 18; n0 += 3) {
      uint32_t e[3][8];
#pragma unroll
      for (int n = 0; n < 3; n++)
#pragma unroll
        for (int i = 0; i < 8; i++)
          asm volatile("ld.shared.u16 %0, [%1];" : "=r"(e[n][i]) : "r"(a + n * 32 + (i >> 1) * DF * 2 + (i & 1) * 16448) : "memory");
#pragma unroll
      for (int n = 0; n < 3; n++)
        if (16 * (n0 + n) + (ht >> 3) < DF)
          asm volatile("st.global.v4.u32 [%0], {%1,%2,%3,%4};" ::"l"(wp + n * 16 * 8192),
                       "r"(__byte_perm(e[n][0], e[n][1], 0x5410)), "r"(__byte_perm(e[n][2], e[n][3], 0x5410)),
                       "r"(__byte_perm(e[n][4], e[n][5], 0x5410)), "r"(__byte_perm(e[n][6], e[n][7], 0x5410)) : "memory");
      a += 96;
      wp += 48 * 8192;
    }
  }
}

struct Ring {
  uint32_t s, ph;
  __device__ __forceinline__ void next() { if (++s == NS - 1) { s = 0; ph ^= 1; } }
};

struct Gemm {
  Ring r;
  uint32_t prev;
  uint32_t dA, dB, bars;
  uint32_t zr;
  bool lead;
  template <int TB, int KSTEP, int TAIL = 0>
  __device__ __forceinline__ void run(float* acc, int n, int accum) {
#pragma unroll 1
    for (int i = 0; i < n; i++) {
      mbar_wait(bars + 8 * r.s, r.ph);
      const uint32_t a = dA + r.s * (STAGE >> 4), w = dB + r.s * (STAGE >> 4);
      wg_fence();
#pragma unroll
      for (int k = 0; k < 4; k++) {
        wgmma128<TB>(acc, a + k * 128, w + k * KSTEP, k ? 1 : accum);
        if (k == TAIL) {
          wg_commit();
          wg_wait<1>();
          if (lead) mbar_arrive(prev);
          wg_fence();
        }
      }
      wg_commit();
      accum = 1;
      prev = bars + 8 * (B_EMPTY + r.s);
      r.next();
      if (!TB && TAIL && i == n - 2) r = {NS - 1, 0};
    }
  }
  __device__ __forceinline__ void drain() {
    wg_wait<0>();
    if (lead) mbar_arrive(prev);
    prev = bars + 8 * B_NONE;
  }
  template <int TB, int KSTEP, class F>
  __device__ __forceinline__ void tail(float* acc, int wg, F&& pre, uint32_t lda, uint32_t bias, uint32_t xdst, uint32_t xfull, int xfree) {
    constexpr int T = TM;
    auto add_bias = [&]() {
      uint32_t bb[8];
      if (TB) {
#pragma unroll
        for (int j = 0; j < 8; j++) bb[j] = lds32(bias + 16 * j);
      } else {
#pragma unroll
        for (int h = 0; h < 2; h++) asm volatile("ld.shared.u16 %0, [%1];" : "=r"(bb[h]) : "r"(bias + 16 * h) : "memory");
      }
#pragma unroll
      for (int j = 0; j < 32; j++)
        acc[j] += TB ? ((j & 1) ? bhi(bb[j >> 2]) : blo(bb[j >> 2])) : blo(bb[(j >> 1) & 1]);
    };
    auto send = [&](int j) {
      const float* a = acc + 32 + 16 * (j & 1) + (j & 2);
      const uint32_t hf = 0x3f003f00u, nz = 0x80008000u;
      st_async4(xdst + j * 4096, hfma2(pack(a[0], a[1]), hf, nz), hfma2(pack(a[4], a[5]), hf, nz), hfma2(pack(a[8], a[9]), hf, nz),
                hfma2(pack(a[12], a[13]), hf, nz), xfull + 4 * (j & 2));
    };
    if (TB && wg) {
      drain();
      keep<32>(acc);
      renew<32>(acc + 32);
      mbar_wait(bars + 8 * xfree);
      add_bias();
      keep<32>(acc);
      uint32_t A[T][16], w[T], em[T];
#pragma unroll
      for (int i = 0; i < T; i++) {
        mbar_wait(bars + 8 * r.s, r.ph);
#pragma unroll
        for (int k = 0; k < 4; k++) ldsm4t(lda + r.s * STAGE + k * 2048, A[i] + 4 * k);
        w[i] = dB + r.s * (STAGE >> 4);
        em[i] = bars + 8 * (B_EMPTY + r.s);
        r.next();
      }
      nb_sync(NB_T, 256);
      wg_fence();
#pragma unroll
      for (int n = 0; n < 4 * T; n++) wgmma64rs<1, TB, 1024, TB>(acc + 32, A[n >> 2] + 4 * (n & 3), w[n >> 2] + 512 + (n & 3) * KSTEP);
      wg_commit();
#pragma unroll
      for (int n = 0; n < 4 * T; n++) {
        wgmma64rs<1, TB, 1024, TB>(acc, A[n >> 2] + 4 * (n & 3), w[n >> 2] + (n & 3) * KSTEP);
        if (n == 3) { wg_commit(); wg_wait<1>(); keep<32>(acc + 32); send(0); wg_fence(); }
        if (n > 3 && n < 7) send(n - 3);
        if (n > 3 && (n & 3) == 3) { wg_commit(); wg_wait<1>(); if (lead) mbar_arrive(em[(n >> 2) - 1]); wg_fence(); }
      }
      wg_commit();
      pre();
      wg_wait<0>();
      keep<32>(acc);
      if (lead) mbar_arrive(em[T - 1]);
    } else {
      if (wg) {
        drain();
        keep<64>(acc);
        add_bias();
        keep<64>(acc);
        nb_sync(NB_T, 256);
      }
      run<TB, KSTEP, 1>(acc, T, 1);
      if (!wg) nb_arrive(NB_T, 256);
      if (!TB) pre();
      mbar_wait(bars + 8 * xfree);
      drain();
      keep<64>(acc);
#pragma unroll
      for (int j = 0; j < 4; j++) send(j);
      if (!wg) {
        add_bias();
        pin<32>(acc, zr);
      }
    }
  }
};

template <bool BY_SM>
__global__ void __cluster_dims__(2, 1, 1) __launch_bounds__(NTHR, 1)
fused_kernel(const __grid_constant__ Params P, const __grid_constant__ CUtensorMap mW1, const __grid_constant__ CUtensorMap mW2,
             const __grid_constant__ CUtensorMap mX1) {
  extern __shared__ __align__(1024) unsigned char smem[];
#define GET_B uint32_t sm_, rk_;                                                                         \
  if (BY_SM) asm volatile("mov.u32 %0, %%smid;" : "=r"(sm_));                                            \
  else asm volatile("mov.u32 %0, %%ctaid.x;" : "=r"(sm_));                                                       \
  asm volatile("mov.u32 %0, %%cluster_ctarank;" : "=r"(rk_));                                            \
  const uint32_t tb_ = P.tab[(sm_ & ~1u) | rk_];                                                         \
  const int b = tb_ & 255, pb = ((tb_ >> 14) & 0x78) | ((tb_ >> 12) & 7);
#define cnt(c) (scr + G_CNT + 128 * (c))
#define ROLE_CTX                                                                                         \
  const uint32_t sb = __shfl_sync(0xffffffffu, (uint32_t)__cvta_generic_to_shared(smem), 0);             \
  int tid;                                                                                               \
  GET_B                                                                                                  \
  asm volatile("mov.u32 %0, %%tid.x;" : "=r"(tid));                                                      \
  const int lane = tid & 31, warp = __shfl_sync(0xffffffffu, tid >> 5, 0);                               \
  const bool main_cta = b < 128, g1_cta = b < 112;                                                       \
  const int rank = b & 1, dt = (b >> 1) & 3, wt = b >> 3;                                  \
  unsigned char* const scr = P.scr;                                                                      \
  auto bar = [&](int i) { return sb + MISC + 8 * i; };                                                   \
  (void)rank; (void)dt; (void)wt; (void)lane; (void)warp; (void)g1_cta; (void)pb;
  uint32_t L[2][8];
  {
    const uint32_t tx = threadIdx.x;
    const unsigned char* xp = (const unsigned char*)P.x + ((tx & 32) * 2048 + (tx >> 6) * 1024 + (tx & 2) * 256 + (tx & 1) * 64 + (tx & 28) * 2);
    GET_B
    (void)b; (void)pb;
    xp += tb_ & 0x1ff000;
    asm volatile("{\n.reg .pred p;\n.reg .u32 c, e;\nsetp.ge.u32 p, %17, 256;\n@p bra XD;\n"
                 "setp.eq.u32 p, %18, 0;\n@p bra XL;\nmov.u32 e, %%clock;\n"
                 "XW:\nmov.u32 c, %%clock;\nsub.u32 c, c, e;\nsetp.lt.u32 p, c, %18;\n@p bra XW;\nXL:\n"
                 "ld.global.nc.v2.u32 {%0,%1}, [%16];\nld.global.nc.v2.u32 {%2,%3}, [%16+128];\n"
                 "ld.global.nc.v2.u32 {%4,%5}, [%16+256];\nld.global.nc.v2.u32 {%6,%7}, [%16+384];\n"
                 "ld.global.nc.v2.u32 {%8,%9}, [%16+32768];\nld.global.nc.v2.u32 {%10,%11}, [%16+32896];\n"
                 "ld.global.nc.v2.u32 {%12,%13}, [%16+33024];\nld.global.nc.v2.u32 {%14,%15}, [%16+33152];\nXD:\n}"
                 : "=r"(L[0][0]), "=r"(L[0][1]), "=r"(L[0][2]), "=r"(L[0][3]), "=r"(L[0][4]), "=r"(L[0][5]), "=r"(L[0][6]), "=r"(L[0][7]),
                   "=r"(L[1][0]), "=r"(L[1][1]), "=r"(L[1][2]), "=r"(L[1][3]), "=r"(L[1][4]), "=r"(L[1][5]), "=r"(L[1][6]), "=r"(L[1][7])
                 : "l"(xp), "r"(tx | ((uint32_t)(uintptr_t)xp & 7u) << 8), "r"(tb_ >> 21));
  }
  if (threadIdx.x < 256) {
    asm volatile("barrier.cluster.arrive.relaxed.aligned;" ::: "memory");
    asm volatile("setmaxnreg.inc.sync.aligned.u32 208;");
    ROLE_CTX
    if (b > 128) return;
    const int g = lane >> 2, t = lane & 3, wg = warp >> 2;
    const uint32_t zr = P.zero & tid;
    const int hprio = (pb >> 3) & 7;
    const int pcol = b == 0 ? 128 : (b & 0x70) | ((b & 7) << 1) | ((b >> 3) & 1);
    const int k1c = 8 * warp + g;
    uint32_t fa[8][4];
    auto fa_consts = [&]() {
      float c, s, dc, ds;
      __sincosf((float)(k1c * t) * 0.09817477042468103f, &s, &c);
      __sincosf((float)(k1c & 15) * 0.39269908169872414f, &ds, &dc);
#pragma unroll
      for (int n = 0; n < 8; n++) {
        fa[n >> 1][2 * (n & 1)] = pack(c, s);
        fa[n >> 1][2 * (n & 1) + 1] = pack(-s, c);
        if (n < 7) rot(c, s, dc, ds);
      }
#pragma unroll
      for (int n = 0; n < 16; n++) fa[4 + (n >> 2)][n & 3] = fa[n >> 2][n & 3] ^ ((g & 1) ? 0x80008000u : 0u);
      keepu<16>(fa[4]);
      pin<16>(fa[4], zr);
    };
    RowConst rc;
    uint32_t hq[2][8];
    unsigned char* hp;
    auto store_h = [&]() {
#pragma unroll
      for (int r = 0; r < 2; r++)
#pragma unroll
        for (int j = 0; j < 4; j++) stg64(hp + r * 4096 + (j >> 1) * 32 * SLOT + (j & 1) * 8192, hq[r][2 * j], hq[r][2 * j + 1]);
      nb_arrive(NB_H, 288);
    };
    if (main_cta) {
      const int row0 = 128 * (pb >> 3) + 64 * (warp & 1) + 4 * (pb & 7) + (warp >> 1);
      const int col = t >> 1;
      hp = scr + G_H + ((2 * col * 32 + (row0 >> 6)) * 2) * 8192 + (row0 & 63) * 128 +
                          (((4 * (t & 1) + (g >> 1)) ^ (row0 & 7)) << 4) + (g & 1) * 8;
      uint32_t sta[4];
      auto row_consts = [&](int lane) {
        const int g = lane >> 2, t = lane & 3, col = t >> 1;
        row_const(rc, lane);
        {
          const uint32_t un = (warp >> 1) * 2 + col, sub = 8 * (warp & 1);
#pragma unroll
          for (int h = 0; h < 2; h++) {
            const int kl = 16 * (t & 1) + 2 * g + h, p = col ? 128 - kl : kl, r7 = (p >> 1) & 7;
            sta[h] = sb + S0 + ((p & 0xf0) + 8 * h + r7) * 128 + ((un ^ r7) << 4) + sub;
          }
          sta[2] = (lane & 29) ? sta[0] : col ? sta[0] - SLOT : sb + XTRA + (un << 4) + sub;
          sta[3] = (uint32_t)(uintptr_t)hp;
        }
        pin<16>(&rc, zr); pin<4>(sta, zr);
      };
      if (hprio >= H_LATE) {
        row_consts(lane);
        fa_consts();
      } else {
        const uint32_t hl = (uint32_t)(uintptr_t)hp;
        pin<1>(&hl, zr);
      }
      float v[2][16], s1[2], s2[2];
#pragma unroll
      for (int r = 0; r < 2; r++) {
        const float piv = blo(__shfl_sync(0xffffffffu, L[r][0], 0));
        s1[r] = 0.f; s2[r] = 0.f;
#pragma unroll
        for (int j = 0; j < 8; j++) { v[r][2 * j] = blo(L[r][j]) - piv; v[r][2 * j + 1] = bhi(L[r][j]) - piv; }
#pragma unroll
        for (int i = 0; i < 16; i++) { s1[r] += v[r][i]; s2[r] = fmaf(v[r][i], v[r][i], s2[r]); }
      }
      {
        const bool hi = lane & 16, q = lane & 8;
        float a = (hi ? s1[1] : s1[0]) + __shfl_xor_sync(0xffffffffu, hi ? s1[0] : s1[1], 16);
        float c = (hi ? s2[1] : s2[0]) + __shfl_xor_sync(0xffffffffu, hi ? s2[0] : s2[1], 16);
        a = (q ? c : a) + __shfl_xor_sync(0xffffffffu, q ? a : c, 8);
#pragma unroll
        for (int o = 4; o > 0; o >>= 1) a += __shfl_xor_sync(0xffffffffu, a, o);
        s1[0] = __shfl_sync(0xffffffffu, a, 0); s2[0] = __shfl_sync(0xffffffffu, a, 8);
        s1[1] = __shfl_sync(0xffffffffu, a, 16); s2[1] = __shfl_sync(0xffffffffu, a, 24);
      }
#pragma unroll
      for (int r = 0; r < 2; r++) {
        s1[r] *= -1.f / DM;
        s2[r] = fmaxf(fmaf(-s1[r], s1[r], s2[r] * (1.f / DM)), 0.f);
        const float a2 = rsqrt_fast(fmaf(s2[r], 1.f + 1e-5f, 1e-10f)), c2 = s1[r] * a2;
#pragma unroll
        for (int j = 0; j < 8; j++) hq[r][j] = pack(fmaf(v[r][2 * j], a2, c2), fmaf(v[r][2 * j + 1], a2, c2));
      }
      if (hprio < H_LATE) store_h();
      if (hprio < H_LATE) row_consts(__float_as_uint(after_here(__uint_as_float(lane), zr)));
      nb_sync(NB_R, 384);
      const float eps = after_here(1e-5f, zr);
#pragma unroll
      for (int r = 0; r < 2; r++) {
        const float a1 = rsqrt_fast(s2[r] + eps), c1 = s1[r] * a1;
#pragma unroll
        for (int j = 0; j < 8; j++) L[r][j] = pack(fmaf(v[r][2 * j], a1, c1), fmaf(v[r][2 * j + 1], a1, c1));
      }
      wg_fence();
      row_step1<2>(sb, L, v);
      if (hprio >= H_LATE) store_h();
      wg_wait<0>();
      row_twiddle<2>(rc, L, v);
      wg_fence();
      row_step2<2>(sb, L, v);
      wg_wait<0>();
      keep<16>(v[0]);
      keep<16>(v[1]);
      const uint32_t cj = col << 31;
      const int stp = col ? -4096 : 4096;
#pragma unroll
      for (int j = 0; j < 4; j++)
#pragma unroll
        for (int h = 0; h < 2; h++) {
          const uint32_t a = (j | h) ? sta[h] + j * stp : sta[2];
          const uint32_t z0 = pack(v[0][4 * j + 2 * h + 1], v[0][4 * j + 2 * h]) ^ cj;
          const uint32_t z1 = pack(v[1][4 * j + 2 * h + 1], v[1][4 * j + 2 * h]) ^ cj;
          if (!(j | h) && !(lane & 29))
            asm volatile("st.shared.v2.u32 [%0], {%1,%2};" ::"r"(a ^ 16), "r"(z0 ^ 0x80000000u), "r"(z1 ^ 0x80000000u) : "memory");
          asm volatile("st.shared.v2.u32 [%0], {%1,%2};" ::"r"(a), "r"(z0), "r"(z1) : "memory");
        }
      fence_async_smem();
      __syncwarp();
      if (lane == 0) mbar_arrive(bar(B_STG));
    } else {
      nb_sync(NB_R, 384);
    }
    if (hprio < H_LATE) fa_consts();
    const uint32_t peer = mapa(sb, rank ^ 1);
    float c[32];
    const uint32_t dB1 = dlo(sb + S1, 1024);
    const uint32_t lda = sb + 8192 + ((lane & 7) + 8 * (lane >> 4)) * 128 + (((2 * (warp & 3) + ((lane >> 3) & 1)) ^ (lane & 7)) << 4);
    Gemm gm;
    gm.r = {0, 0}; gm.bars = bar(0); gm.prev = bar(B_NONE); gm.lead = (tid & 127) == 0; gm.zr = zr;
    if (g1_cta) {
      float acc[64];
      gm.dA = dlo(sb + wg * 8192, 8192); gm.dB = dlo(sb + SLOT, 8192);
      gm.run<1, 128>(acc, 16 - TM, 0);
      gm.tail<1, 128>(acc, wg, [&]() { mbar_wait(bar(B_CF)); }, lda, sb + BIAS + 4 * t, peer + S0 + tid * 16, peer + MISC + 8 * B_XFULL1 + 16 * wg, B_XFREE1);
      unsigned char* up = scr + G_U + (dt * 28 + 2 * wt + rank) * SLOT + warp * 2048 + lane * 4;
#pragma unroll
      for (int h = 0; h < 2; h++) {
        mbar_wait(bar(B_XFULL1 + h) + 16 * wg);
        const uint4 oa = lds128(sb + S0 + tid * 16 + h * 8192), ob = lds128(sb + S0 + tid * 16 + h * 8192 + 4096);
        const uint32_t o[8] = {oa.x, oa.y, oa.z, oa.w, ob.x, ob.y, ob.z, ob.w};
        float y[16], th[16];
#pragma unroll
        for (int i = 0; i < 16; i++) {
          y[i] = fmaf(acc[4 * (i >> 1) + 2 * h + (i & 1)], 0.5f, (i & 1) ? bhi(o[i >> 1]) : blo(o[i >> 1]));
          th[i] = tanh_fast(y[i] * fmaf(y[i] * y[i], 0.285419265090401f, 1.5957691216057308f));
        }
#pragma unroll
        for (int nt = 0; nt < 8; nt++)
          stg32(up + nt * 128 + h * 1024, pack(fmaf(y[2 * nt], th[2 * nt], y[2 * nt]), fmaf(y[2 * nt + 1], th[2 * nt + 1], y[2 * nt + 1])));
      }
      nb_arrive(NB_U, 288);
    } else if (main_cta) {
      mbar_wait(bar(B_XFREE1));
    }
    if (!(g1_cta && wg)) mbar_wait(bar(B_CF));
    wg_fence();
    wgmma64rs<0, 0, 128>(c, fa[0], dB1);
#pragma unroll
    for (int i = 1; i < 8; i++) wgmma64rs<1, 0, 128>(c, fa[i], dB1 + i * (2048 >> 4));
    wg_commit();
    float twc[8], tws[8], rho;
    uint32_t wo[4];
    {
      float w = after_here(0.0030679615757712823f, zr);
      float c, s, dc, ds;
      __sincosf(fmaf((float)pcol, 2.f * w, 0.7853981633974483f), &ds, &dc);
      rho = __fdividef(dc, ds);
      w *= (float)k1c;
      __sincosf(w * (float)t, &s, &c);
      c *= ds * 0.0013810679320049757f; s *= ds * 0.0013810679320049757f;
      __sincosf(w * 4.f, &ds, &dc);
#pragma unroll
      for (int n = 0; n < 8; n++) {
        twc[n] = c; tws[n] = s;
        if (n < 7) rot(c, s, dc, ds);
      }
      const int j0 = k1c + 64 * t, jn = SEQ - j0;
      wo[0] = sb + S3 + (j0 ^ (t << 3)) * 4;
      wo[1] = sb + S3 + 8192 + (jn ^ ((jn >> 3) & 24)) * 4;
      wo[2] = j0 ? wo[1] : wo[1] - 8192;
      wo[3] = __float_as_uint(rho) ^ __float_as_uint(c) ^ __float_as_uint(s);
      pin<4>(wo, zr);
    }
    wg_wait<0>();
    keep<32>(c);
    if ((tid & 127) == 0) mbar_arrive(bar(B_S1));
    uint32_t ap[16];
    float d[32];
    const uint32_t dG = dlo(sb + S2, 128);
#pragma unroll
    for (int nt = 0; nt < 8; nt++) {
      ap[2 * nt] = pack(c[4 * nt] * twc[nt] + c[4 * nt + 2] * tws[nt], c[4 * nt + 2] * twc[nt] - c[4 * nt] * tws[nt]);
      ap[2 * nt + 1] = pack(c[4 * nt + 1] * twc[nt] + c[4 * nt + 3] * tws[nt], c[4 * nt + 3] * twc[nt] - c[4 * nt + 1] * tws[nt]);
      if (nt & 1) {
        wg_fence();
        if (nt == 1) wgmma64rs<0, 0, 1024>(d, ap, dG); else wgmma64rs<1, 0, 1024>(d, ap + 2 * nt - 2, dG + (nt >> 1) * (256 >> 4));
      }
    }
    wg_commit();
    uint32_t wq[16];
    mbar_wait(bar(B_WQ));
#pragma unroll
    for (int i = 0; i < 8; i++) { wq[2 * i] = lds32(wo[0] + i * 1024); wq[2 * i + 1] = lds32(wo[i ? 1 : 2] - i * 1024); }
    wg_wait<0>();
    keep<32>(d);
#pragma unroll
    for (int nt = 0; nt < 8; nt++) {
      const float ar = d[4 * nt], ai = d[4 * nt + 1], br = d[4 * nt + 2], bi = d[4 * nt + 3];
      const float w1r = blo(wq[2 * nt]), w1i = bhi(wq[2 * nt]), w2r = blo(wq[2 * nt + 1]), w2i = bhi(wq[2 * nt + 1]);
      const float pr = fmaf(rho, ar, -bi), pi = fmaf(rho, ai, br), qr = fmaf(rho, br, -ai), qi = fmaf(rho, bi, ar);
      const float xr = pr * w1r - pi * w1i, xi = pr * w1i + pi * w1r, yr = qr * w2r + qi * w2i, yi = qi * w2r - qr * w2i;
      ap[2 * nt] = pack(fmaf(rho, xi, -yr), fmaf(rho, xr, yi));
      ap[2 * nt + 1] = pack(fmaf(rho, yi, -xr), fmaf(rho, yr, xi));
      if (nt & 1) {
        wg_fence();
        if (nt == 1) wgmma64rs<0, 0, 1024>(c, ap, dG); else wgmma64rs<1, 0, 1024>(c, ap + 2 * nt - 2, dG + (nt >> 1) * (256 >> 4));
      }
    }
    wg_commit();
#pragma unroll
    for (int i = 0; i < 8; i++) {
      const uint32_t cc = __byte_perm(fa[i][0], fa[i][2], 0x5410), ss = __byte_perm(fa[i][0], fa[i][2], 0x7632);
      fa[i][3] = __byte_perm(fa[i][1], fa[i][3], 0x7632);
      fa[i][0] = cc; fa[i][1] = ss ^ 0x80008000u; fa[i][2] = ss;
      keepu<4>(fa[i]);
    }
    mbar_wait(bar(B_S1));
    wg_wait<0>();
    keep<32>(c);
#pragma unroll
    for (int nt = 0; nt < 8; nt++) {
      ap[2 * nt] = pack(c[4 * nt] * twc[nt] + c[4 * nt + 1] * tws[nt], c[4 * nt + 2] * twc[nt] + c[4 * nt + 3] * tws[nt]);
      ap[2 * nt + 1] = pack(c[4 * nt + 1] * twc[nt] - c[4 * nt] * tws[nt], c[4 * nt + 3] * twc[nt] - c[4 * nt + 2] * tws[nt]);
    }
    {
      const int r = lane & 7, mi = lane >> 3;
      const uint32_t a = sb + S1 + warp * 2048 + (mi & 1) * 1024 + (mi >> 1) * 128 + (2 * (r & 3) + (r >> 2)) * 16;
#pragma unroll
      for (int i = 0; i < 4; i++) stsm4(a + i * 256, ap[4 * i], ap[4 * i + 1], ap[4 * i + 2], ap[4 * i + 3]);
    }
    fence_async_smem();
    nb_sync(NB_C, 256);
    wg_fence();
    wgmma64rs<0, 1, 128>(c, fa[0], dB1);
#pragma unroll
    for (int i = 1; i < 8; i++) wgmma64rs<1, 1, 128>(c, fa[i], dB1 + i * (2048 >> 4));
    wg_commit();
    unsigned char* zq = scr + G_Z + (k1c >> 2) * 8 * SLOT + (pcol & 127) * 128 + (((4 * t + (g & 3)) ^ ((pcol >> 1) & 15)) << 3);
    wg_wait<0>();
    keep<32>(c);
    if ((tid & 127) == 0) mbar_arrive(bar(B_S4));
    const bool zlate = g1_cta && (pcol & 127);
    if (!zlate) {
      if (pcol & 127) {
#pragma unroll
        for (int nt = 0; nt < 8; nt++) stg64(zq + nt * SLOT, pack(c[4 * nt], c[4 * nt + 2]), pack(-c[4 * nt + 1], c[4 * nt + 3]));
      } else {
#pragma unroll
        for (int nt = 0; nt < 8; nt++)
          stg32(zq + nt * SLOT + (pcol >> 5), pcol ? pack(-c[4 * nt + 1], c[4 * nt + 3]) : pack(c[4 * nt], c[4 * nt + 2]));
      }
      nb_arrive(NB_Z, 288);
    }
    if (main_cta) {
      float acc[64];
      gm.dA = dlo(sb + SLOT + wg * 8192, 8192); gm.dB = dlo(sb, 128);
      const int nz = ZK + (wg ? ZST : 0);
      auto store_z = [&](int n0) {
#pragma unroll
        for (int nt = n0; nt < n0 + 4; nt++)
          asm volatile("{\n.reg .pred p;\nsetp.ne.u32 p, %3, 0;\n@p st.global.v2.u32 [%0], {%1,%2};\n}" ::"l"(zq + nt * SLOT),
                       "r"(pack(c[4 * nt], c[4 * nt + 2])), "r"(pack(-c[4 * nt + 1], c[4 * nt + 3])), "r"((uint32_t)zlate) : "memory");
      };
      mbar_wait(bar(B_FULL) + 8 * gm.r.s, gm.r.ph);
      store_z(0);
      gm.run<0, 16>(acc, 1, 0);
      store_z(4);
      if (zlate) nb_arrive(NB_Z, 288);
      gm.run<0, 16>(acc, nz - 1, 1);
      gm.drain();
      row_ifft<2>(rc, sb, scr, b, lane, warp >> 1, 2 * (warp & 1));
      gm.run<0, 16>(acc, 14 - TM - nz, 1);
      const int fo = (wt * 128 + warp * 16 + (lane >> 3)) * 1024 + (dt * 2 + rank) * 128 + (lane & 7) * 16;
      uint4 xv[4];
      auto load_x = [&]() {
#pragma unroll
      for (int i = 0; i < 4; i++)
        asm volatile("ld.global.nc.L1::no_allocate.v4.u32 {%0,%1,%2,%3}, [%4];" : "=r"(xv[i].x), "=r"(xv[i].y), "=r"(xv[i].z), "=r"(xv[i].w)
                     : "l"((const unsigned char*)P.x + fo + i * 4096) : "memory");
      };
      gm.tail<0, 16>(acc, wg, load_x, 0, sb + BIAS + 128 + (warp * 16 + g) * 2, peer + S1 + tid * 16, peer + MISC + 8 * B_XFULL2 + 16 * wg,
                     B_XFREE2);
      const uint32_t ga = sb + S1 + warp * 512;
      uint4 gv[4], sv[4];
      auto load_s = [&]() {
#pragma unroll
        for (int i = 0; i < 4; i++)
          asm volatile("ld.relaxed.gpu.global.v4.u32 {%0,%1,%2,%3}, [%4];" : "=r"(sv[i].x), "=r"(sv[i].y), "=r"(sv[i].z), "=r"(sv[i].w)
                       : "l"(scr + G_S + fo + i * 4096) : "memory");
      };
      bool have_s = false;
#pragma unroll
      for (int h = 0; h < 2; h++) {
        mbar_wait(bar(B_XFULL2 + h) + 16 * wg);
        if (!have_s && mbar_test(bar(B_FIN))) { load_s(); have_s = true; }
        const uint4 oa = lds128(sb + S1 + tid * 16 + h * 8192), ob = lds128(sb + S1 + tid * 16 + h * 8192 + 4096);
        const uint32_t o[8] = {oa.x, oa.y, oa.z, oa.w, ob.x, ob.y, ob.z, ob.w};
        uint32_t gs[8];
#pragma unroll
        for (int nt = 0; nt < 8; nt++) {
          const float y0 = fmaf(acc[4 * nt + 2 * h], 0.5f, blo(o[nt])), y1 = fmaf(acc[4 * nt + 2 * h + 1], 0.5f, bhi(o[nt]));
          gs[nt] = pack(fmaf(y0, tanh_fast(y0), y0), fmaf(y1, tanh_fast(y1), y1));
        }
        const uint32_t a = ga + h * 8192 + (lane & 4) * 1024 + (lane & 3) * 128 + (((lane >> 3) ^ (lane & 7)) << 4);
        __syncwarp();
        stsm4(a, gs[0], gs[1], gs[2], gs[3]);
        stsm4(a ^ 64, gs[4], gs[5], gs[6], gs[7]);
      }
      __syncwarp();
#pragma unroll
      for (int i = 0; i < 4; i++) gv[i] = lds128(ga + i * 4096 + (lane >> 3) * 128 + (((lane & 7) ^ (4 * (i & 1) + (lane >> 3))) << 4));
      if (!have_s) { mbar_wait(bar(B_FIN)); load_s(); }
#pragma unroll
      for (int i = 0; i < 4; i++)
        asm volatile("st.global.v4.u32 [%0], {%1,%2,%3,%4};" ::"l"((unsigned char*)P.out + fo + i * 4096), "r"(hfma2(sv[i].x, gv[i].x, xv[i].x)),
                     "r"(hfma2(sv[i].y, gv[i].y, xv[i].y)), "r"(hfma2(sv[i].z, gv[i].z, xv[i].z)), "r"(hfma2(sv[i].w, gv[i].w, xv[i].w)) : "memory");
    }
  } else if (threadIdx.x < 384) {
    asm volatile("setmaxnreg.dec.sync.aligned.u32 56;");
    ROLE_CTX
    if (b > 128) return;
    asm volatile("barrier.cluster.arrive.relaxed.aligned;" ::: "memory");
    const int hw = warp - 8, ht = tid - 256, kg = ht & 3;
    {
      const int pos = (ht >> 2) & 7, k1 = 2 * pos + (hw >> 1);
      float c, s, dc, ds;
      __sincosf((float)((k1 * 2 * kg + 4 * (hw & 1)) & 15) * 0.39269908169872414f, &s, &c);
      __sincosf((float)k1 * 0.39269908169872414f, &ds, &dc);
      const uint32_t e0 = pack(c, s), sg = (hw >> 1) ? 0x80008000u : 0u;
      rot(c, s, dc, ds);
      const uint32_t e1 = pack(c, s);
      asm volatile("st.shared.v4.u32 [%0], {%1,%2,%3,%4};" ::"r"(sb + RMAT + hw * 512 + kg * 128 + pos * 16), "r"(e0), "r"(e1),
                   "r"(e0 ^ sg), "r"(e1 ^ sg) : "memory");
      fence_async_smem();
    }
    asm volatile("barrier.cluster.wait.aligned;" ::: "memory");
    nb_arrive(NB_R, 384);
    if (main_cta && !g1_cta) {
      transpose_w(sb, scr, b, ht);
      nb_sync(NB_HLP, 128);
      if (hw == 3 && elect_one()) { signal(cnt(C_W), 1); mbar_arrive(bar(B_WDONE)); }
      __syncwarp();
    }
    if (g1_cta) mbar_wait(bar(B_STG));
    {
      const int k2 = ht >> 2;
      float c, s, dc, ds;
      __sincosf((float)((k2 * 8 * kg) & 31) * 0.19634954084936207f, &s, &c);
      __sincosf((float)k2 * 0.19634954084936207f, &ds, &dc);
#pragma unroll
      for (int q = 0; q < 2; q++) {
        uint32_t re[4], im[4];
#pragma unroll
        for (int i = 0; i < 4; i++) {
          re[i] = pack(c, s); im[i] = pack(-s, c);
          rot(c, s, dc, ds);
        }
        const uint32_t a = sb + S2 + ((k2 >> 2) * 8 + kg * 2 + q) * 128 + (k2 & 3) * 32;
        asm volatile("st.shared.v4.u32 [%0], {%1,%2,%3,%4};" ::"r"(a), "r"(re[0]), "r"(re[1]), "r"(re[2]), "r"(re[3]) : "memory");
        asm volatile("st.shared.v4.u32 [%0], {%1,%2,%3,%4};" ::"r"(a + 16), "r"(im[0]), "r"(im[1]), "r"(im[2]), "r"(im[3]) : "memory");
      }
      if (!main_cta) {
        mbar_wait(bar(B_WQ));
#pragma unroll 1
        for (int i = ht; i < 2 * 1025; i += 128) {
          const int j = i >> 1, jn = (SEQ - j) & (SEQ - 1);
          const uint32_t a0 = sb + S3 + (i & 1) * 8192, a = a0 + (j ^ ((j >> 3) & 24)) * 4, an = a0 + (jn ^ ((jn >> 3) & 24)) * 4;
          const uint32_t u = lds32(a), v = lds32(an), w = pack(0.5f * (blo(u) + blo(v)), 0.5f * (bhi(u) - bhi(v)));
          asm volatile("st.shared.u32 [%0], %1;" ::"r"(an), "r"(w ^ 0x80000000u) : "memory");
          asm volatile("st.shared.u32 [%0], %1;" ::"r"(a), "r"(w) : "memory");
        }
      }
      fence_async_smem();
      __syncwarp();
      if (lane == 0) mbar_arrive(bar(B_CF));
    }
  } else {
    asm volatile("setmaxnreg.dec.sync.aligned.u32 40;");
    ROLE_CTX
    if (b > 128) {
      const uint32_t t0 = clk();
      while (warp == 12 && clk() - t0 < 6000) __nanosleep(200);
      if (BY_SM && warp == 12 && elect_one()) {
#pragma unroll 1
        for (int n = 16 + b - 129; n < 40; n += 3)
          asm volatile("cp.async.bulk.prefetch.L2.global [%0], %1;" ::"l"((const unsigned char*)P.w2 +
                       ((n & 1) * 896 + (n >> 1) * 16) * (SEQ * 2)), "r"(65536) : "memory");
      }
      return;
    }
    if (warp == 12) {
      if (elect_one()) {
#pragma unroll
        for (int i = 0; i <= B_NONE; i++) mbar_init(bar(i), i < NS ? 1 : i < 2 * NS ? 2 : 0x7ffff);
        if (!g1_cta) {
#pragma unroll
          for (int i = B_WCH; i < B_WDONE; i++) mbar_init(bar(i), 1);
        }
        mbar_init(bar(B_WDONE), 1);
        asm volatile("fence.mbarrier_init.release.cluster;" ::: "memory");
      }
      __syncwarp();
      asm volatile("barrier.cluster.arrive.relaxed.aligned;" ::: "memory");
      if (main_cta && elect_one()) {
        Ring r = {0, 1};
        if (g1_cta) {
          const int c0 = wt * 128 + rank * 64;
#pragma unroll 1
          for (int k = rank * 1024; k < rank * 1024 + 1024; k += 64) {
            const uint32_t d = sb + SLOT + r.s * STAGE, f = bar(B_FULL) + 8 * r.s;
            mbar_wait(f + 8 * NS, r.ph);
            tma2d(d, &mW1, c0, k, f);
            tma2d(d + 8192, &mW1, c0 ^ 64, k, f);
            r.next();
          }
        } else {
#pragma unroll 1
          for (int i = 0; i < 4; i++) {
            if (i >= 2) mbar_wait(bar(B_WCH + i - 2));
            const int go = ((b - 112) * 4 + i) * 16448;
            bulk_load(sb + i * WCH, (const unsigned char*)P.wr + go, 16448, bar(B_WCH + i));
            bulk_load(sb + i * WCH + 16448, (const unsigned char*)P.wi + go, 16448, bar(B_WCH + i));
            mbar_expect(bar(B_WCH + i), 32896);
          }
          mbar_wait(bar(B_WDONE));
        }
        if (g1_cta) mbar_wait(bar(B_FULL), 1);
#pragma unroll 1
        for (int k = rank * 896; k < rank * 896 + 896; k += 64) {
          const uint32_t d = sb + SLOT + r.s * STAGE, f = bar(B_FULL) + 8 * r.s;
          if (k == rank * 896 + 256) mbar_wait(bar(B_WDONE));
          mbar_wait(f + 8 * NS, r.ph);
          tma2d(d, &mW2, wt * 128, k, f);
          tma2d(d + 8192, &mW2, wt * 128 + 64, k, f);
          r.next();
          if (k == rank * 896 + 768) r = {NS - 1, 0};
          if (k == rank * 896 + 64 * (GZ - 1)) mbar_wait(bar(B_Z));
        }
      }
    } else if (warp == 15) {
      if (elect_one()) {
#pragma unroll
        for (int i = B_STG; i < B_COUNT; i++) mbar_init(bar(i), i == B_STG ? 8 : i == B_CF ? 5 : i <= B_S1 ? 2 : 1);
        asm volatile("fence.mbarrier_init.release.cluster;" ::: "memory");
      }
      __syncwarp();
      asm volatile("barrier.cluster.arrive.relaxed.aligned;" ::: "memory");
      const void *ch = cnt(C_H + (pb >> 6)), *cu = cnt(C_U + dt * 2 + (wt >= 7)), *cz = cnt(C_Z), *cs = cnt(C_S + (wt & 15));
      const unsigned ih = 1u << (4 * ((pb >> 3) & 7)), iu = 1u << (2 * (wt >= 7 ? wt - 7 : wt) + rank);
      asm volatile("" : "+l"(ch), "+l"(cu), "+l"(cz), "+l"(cs));
      if (main_cta) {
        nb_sync(NB_H, 288);
        if (elect_one()) signal(ch, ih);
        __syncwarp();
      }
      if (g1_cta) {
        nb_sync(NB_U, 288);
        if (elect_one()) { signal(cu, iu); mbar_arrive(bar(B_WDONE)); }
        __syncwarp();
      }
      nb_sync(NB_Z, 288);
      if (elect_one()) signal(cz, main_cta ? 1 : 128);
      __syncwarp();
      if (main_cta) {
        nb_sync(NB_S, 288);
        if (elect_one()) signal(cs, 1);
      }
    } else {
      asm volatile("barrier.cluster.arrive.relaxed.aligned;" ::: "memory");
      const unsigned ep = ld_relaxed(cnt(C_EPOCH));
      asm volatile("barrier.cluster.wait.aligned;" ::: "memory");
      if (warp == 13) {
        if (main_cta && elect_one()) {
          Ring r = {0, 1};
          unsigned seen = 0;
          if (g1_cta) {
            const unsigned char* src = scr + G_H + (dt * 32 + rank * 16) * SLOT;
#pragma unroll 1
            for (int i = 0; i < 16; i++) {
              const uint32_t d = sb + r.s * STAGE, f = bar(B_FULL) + 8 * r.s;
              mbar_wait(f + 8 * NS, r.ph);
              poll(cnt(C_H + rank), ep * 0x88888888u, 8u << (2 * (i & 14)), seen);
              bulk_load(d, src, SLOT, f);
              mbar_expect(f, STAGE);
              src += SLOT;
              r.next();
            }
          } else {
            mbar_wait(bar(B_WDONE));
          }
          seen = 0;
          const unsigned char* src = scr + G_U + (dt * 28 + rank * 14) * SLOT + rank * 8192;
          const int oth = rank ? -8192 : 8192;
#pragma unroll 1
          for (int i = 0; i < 14; i++) {
            const uint32_t d = sb + r.s * STAGE, f = bar(B_FULL) + 8 * r.s;
            mbar_wait(f + 8 * NS, r.ph);
            poll(cnt(C_U + dt * 2 + rank), ep * 0x3fffu, 1u << i, seen);
            bulk_load(d, src, 8192, f);
            bulk_load(d + 8192, src + oth, 8192, f);
            mbar_expect(f, STAGE);
            src += SLOT;
            r.next();
            if (i == 12) r = {NS - 1, 0};
            if (i == GZ - 1) mbar_wait(bar(B_Z));
          }
        }
      } else if (elect_one()) {
        const uint32_t peer = mapa(sb, rank ^ 1);
#pragma unroll
        for (int i = 0; i < 8; i++) mbar_expect(bar(B_XFULL1 + i), SLOT / 4);
        if (main_cta) {
          bulk_load(sb + BIAS, P.b1 + (g1_cta ? wt : 0) * 128 + rank * 64, 128, bar(B_XFREE1));
          bulk_load(sb + BIAS + 128, P.b2 + wt * 128, 256, bar(B_XFREE1));
          mbar_expect(bar(B_XFREE1), 388);
          prefetch_map(&mX1);
          mbar_wait(bar(B_STG));
          if (g1_cta) mbar_wait(bar(B_FULL + 3));
          bulk_store(scr + G_X1 + 128 * SLOT + pb * 128, sb + XTRA, 128);
          const uint32_t t1 = clk();
#pragma unroll 1
          for (int n = 0; n < 4; n++) {
            wait_until(t1, n * X1_DT);
            tma2d_store(&mX1, pb * 64, 32 * n, sb + S0 + n * 4096);
          }
          bulk_commit();
          bulk_wait_all();
          asm volatile("st.async.weak.shared::cluster.mbarrier::complete_tx::bytes.b32 [%0], %1, [%2];" ::"r"(peer + WHO), "r"(b),
                       "r"(peer + MISC + 8 * B_XFREE1) : "memory");
          mbar_arrive_cluster(peer + MISC + 8 * B_XFREE1);
          signal(cnt(C_X), 1);
          prefetch_map(&mW2);
        }
        poll(cnt(C_X), ep * 128, 128);
        bulk_load(sb + S1, scr + G_X1 + b * SLOT, SLOT, bar(B_CF));
        mbar_expect(bar(B_CF), SLOT);
        const int pcol = b == 0 ? 128 : (b & 0x70) | ((b & 7) << 1) | ((b >> 3) & 1);
        const uint32_t wb = bar(B_WQ);
        poll(cnt(C_W), ep * 16, 16);
        if (g1_cta) mbar_wait(bar(B_XFULL1));
        bulk_load(sb + S3, scr + G_WT + pcol * 8192, 8192, wb);
        bulk_load(sb + S3 + 8192, scr + G_WT + (256 - pcol) * 8192, 8192, wb);
        mbar_expect(wb, SLOT);
        if (main_cta) {
          mbar_wait(bar(B_XFREE1));
          asm volatile("{\n.reg .pred p;\nsetp.ne.u32 p, %0, %1;\n@p trap;\n}" ::"r"(lds32(sb + WHO)), "r"(b ^ 1));
          mbar_wait(bar(B_S4));
          mbar_arrive_cluster(peer + MISC + 8 * B_XFREE2);
          poll(cnt(C_Z), ep * 256, 256);
          bulk_load(sb + S0, scr + G_Z + b * SLOT, SLOT, bar(B_Z));
          mbar_expect(bar(B_Z), SLOT);
          if (b == 0) asm volatile("st.relaxed.gpu.global.u32 [%0], %1;" ::"l"(cnt(C_EPOCH)), "r"(ep + 1) : "memory");
          poll(cnt(C_S + wt), ep * 8, 8);
          mbar_arrive(bar(B_FIN));
        }
      }
    }
  }
}

typedef CUresult (*EncodeFn)(CUtensorMap*, CUtensorMapDataType, cuuint32_t, void*, const cuuint64_t*, const cuuint64_t*,
                             const cuuint32_t*, const cuuint32_t*, CUtensorMapInterleave, CUtensorMapSwizzle,
                             CUtensorMapL2promotion, CUtensorMapFloatOOBfill);

CUtensorMap make_map(EncodeFn enc, const void* p, int inner, int outer, int box_rows) {
  CUtensorMap m;
  cuuint64_t dims[2] = {(cuuint64_t)inner, (cuuint64_t)outer};
  cuuint64_t st[1] = {(cuuint64_t)inner * 2};
  cuuint32_t box[2] = {64u, (cuuint32_t)box_rows};
  cuuint32_t es[2] = {1, 1};
  enc(&m, CU_TENSOR_MAP_DATA_TYPE_BFLOAT16, 2, const_cast<void*>(p), dims, st, box, es, CU_TENSOR_MAP_INTERLEAVE_NONE,
      CU_TENSOR_MAP_SWIZZLE_128B, CU_TENSOR_MAP_L2_PROMOTION_L2_128B, CU_TENSOR_MAP_FLOAT_OOB_FILL_NONE);
  return m;
}

__global__ void probe_kernel() {}
bool place_tpcs(int* slot) {
  int dev = 0, sms = 0, fit[17] = {};
  cudaGetDevice(&dev);
  cudaDeviceGetAttribute(&sms, cudaDevAttrMultiProcessorCount, dev);
  if (sms != NCTA) return false;
  cudaFuncSetAttribute(probe_kernel, cudaFuncAttributeMaxDynamicSharedMemorySize, SMEM_BYTES);
  cudaFuncSetAttribute(probe_kernel, cudaFuncAttributeNonPortableClusterSizeAllowed, 1);
  for (int c = 2; c <= 16; c++) {
    cudaLaunchConfig_t cfg = {};
    cudaLaunchAttribute at;
    at.id = cudaLaunchAttributeClusterDimension;
    at.val.clusterDim.x = c; at.val.clusterDim.y = 1; at.val.clusterDim.z = 1;
    cfg.gridDim = dim3(c); cfg.blockDim = dim3(32); cfg.dynamicSmemBytes = SMEM_BYTES; cfg.attrs = &at; cfg.numAttrs = 1;
    if (cudaOccupancyMaxActiveClusters(&fit[c], probe_kernel, &cfg) != cudaSuccess) {
      (void)cudaGetLastError();
      return false;
    }
  }
  int num[10] = {}, size[66], ng = 0;
  num[9] = fit[9] - fit[10];
  for (int t = 8; t >= 1; t--) {
    num[t] = fit[2 * t];
    for (int u = t + 1; u <= 9; u++) num[t] -= num[u] * (u / t);
  }
  for (int t = 1; t <= 9; t++)
    if (num[t] < 0 || num[t] > 66) return false;
  if (fit[2] != 66) return false;
  for (int t = 2; t <= 9; t++)
    for (int i = 0; i < num[t]; i++) size[ng++] = t;
  int first[67], tpc = 0;
  first[ng] = 0;
  for (int g = ng - 1; g >= 0; g--) first[g] = first[g + 1] + (size[g] < 8 ? size[g] : 8);
  int extra = first[0] + num[1];
  for (int r = 0; r < 9; r++)
    for (int g = 0; g < ng; g++)
      if (size[g] > r) slot[tpc++] = r < 8 ? first[g + 1] + r : extra++;
  for (int i = first[0]; tpc < 66;) slot[tpc++] = i++;
  return true;
}

}

extern "C" void kernel_launch(void* const* d_in, const int* in_sizes, int n_in, void* d_out, int out_size) {
  (void)in_sizes; (void)n_in; (void)out_size;
  static EncodeFn enc = nullptr;
  static void* scr = nullptr;
  static bool by_sm = false;
  static int slot[66];
  if (!enc) {
    void* fn = nullptr;
    cudaDriverEntryPointQueryResult q;
    cudaGetDriverEntryPoint("cuTensorMapEncodeTiled", &fn, cudaEnableDefault, &q);
    enc = (EncodeFn)fn;
    cudaGetSymbolAddress(&scr, g_scr);
    cudaFuncSetAttribute(fused_kernel<true>, cudaFuncAttributeMaxDynamicSharedMemorySize, SMEM_BYTES);
    cudaFuncSetAttribute(fused_kernel<false>, cudaFuncAttributeMaxDynamicSharedMemorySize, SMEM_BYTES);
    by_sm = place_tpcs(slot);
  }
  Params P;
  P.x = (const __nv_bfloat16*)d_in[0];
  P.wr = (const __nv_bfloat16*)d_in[1];
  P.wi = (const __nv_bfloat16*)d_in[2];
  P.b1 = (const __nv_bfloat16*)d_in[5];
  P.w2 = (const __nv_bfloat16*)d_in[6];
  P.b2 = (const __nv_bfloat16*)d_in[7];
  P.scr = (unsigned char*)scr;
  P.out = d_out;
  P.zero = 0;
  const int order[14] = {0, 8, 1, 9, 2, 10, 3, 11, 4, 12, 5, 13, 6, 7};
  for (int i = 0; i < NCTA; i++) {
    const int b = by_sm ? 2 * slot[i >> 1] + (i & 1) : i, idx = (b & 15) * 7 + (b >> 4);
    const int pb = b < 112 ? order[idx >> 3] * 8 + (idx & 7) : b & 127;
    P.tab[i] = b | ((pb & 0x78) << 14) | ((pb & 7) << 12) | ((X_ST * ((pb >> 3) & 7)) << 21);
  }
  const CUtensorMap mW1 = make_map(enc, d_in[4], FF, SEQ, 64);
  const CUtensorMap mW2 = make_map(enc, d_in[6], SEQ, FF, 64);
  const CUtensorMap mX1 = make_map(enc, P.scr + G_X1, 8192, 129, 32);
  if (by_sm) fused_kernel<true><<<NCTA, NTHR, SMEM_BYTES, cudaStreamPerThread>>>(P, mW1, mW2, mX1);
  else fused_kernel<false><<<NCTA - 2, NTHR, SMEM_BYTES, cudaStreamPerThread>>>(P, mW1, mW2, mX1);
}
```
